```python
import torch

def _softmax(x, axis=-1):
    return torch.softmax(x, dim=axis)

def _gelu(x):
    return torch.nn.functional.gelu(x, approximate='tanh')

def _silu(x):
    return torch.nn.functional.silu(x)

def _sigmoid(x):
    return torch.sigmoid(x)

def _layernorm(x, axis=-1, eps=1e-05):
    m = x.mean(dim=axis, keepdim=True)
    v = x.var(dim=axis, keepdim=True, unbiased=False)
    return (x - m) / torch.sqrt(v + eps)

def _scatter_add(tgt, idx, src, axis=0):
    return tgt.clone().index_add_(axis, idx, src)

def _segment_sum(src, seg, n):
    out = torch.zeros((n,) + src.shape[1:], dtype=src.dtype)
    return out.index_add_(0, seg, src)

def _pad(x, pw):
    flat = tuple((v for pair in reversed(pw) for v in pair))
    return torch.nn.functional.pad(x, flat)
kernel_name = 'gather_scatter__tensor_product_equiv_equiformer__graph'

def setup_inputs():

    _w = lambda a: (lambda t: t.to(torch.bfloat16) if t.is_floating_point() else t)(torch.as_tensor(a))
    N, deg, C, De = (25000, 32, 64, max(0, 1))
    E = N * deg
    src = (lambda lo, hi, *s: torch.randint(lo, hi, s))(0, N, E).to(torch.int64)
    dst = (lambda lo, hi, *s: torch.randint(lo, hi, s))(0, N, E).to(torch.int64)
    rvec = (lambda *s: torch.randn(*s, dtype=torch.bfloat16) * 0.05)(E, 3).to(float)
    rn = (torch.linalg.norm(rvec, dim=-1, keepdim=True) + 1e-06).to(float)
    rhat = (rvec / rn).to(float)
    eps = torch.zeros((3, 3, 3), dtype=float)
    eps[0, 1, 2] = eps[1, 2, 0] = eps[2, 0, 1] = 1.0
    eps[0, 2, 1] = eps[2, 1, 0] = eps[1, 0, 2] = -1.0
    return {'x': _w((lambda *s: torch.randn(*s, dtype=torch.bfloat16) * 0.4)(N, 4 * C).to(float)), 'rhat': _w(rhat), 'e_attr': _w((lambda *s: torch.randn(*s, dtype=torch.bfloat16) * 0.4)(E, De).to(float)), 'src': _w(src), 'dst': _w(dst), 'w_rad': _w((lambda *s: torch.randn(*s, dtype=torch.bfloat16) * 0.4)(De, 5 * C).to(float)), 'w_si0': _w((lambda *s: torch.randn(*s, dtype=torch.bfloat16) * 0.4)(2 * C, C).to(float)), 'w_si1': _w((lambda *s: torch.randn(*s, dtype=torch.bfloat16) * 0.05)(3 * C, C).to(float)), 'cg_eps': _w(eps)}

def reference(x, rhat, e_attr, src, dst, w_rad, w_si0, w_si1, cg_eps):
    N = x.shape[0]
    C = w_si0.shape[1]
    E = rhat.shape[0]
    x0 = x[:, :C].clone()
    x1 = x[:, C:].reshape(N, 3, C)
    R = (e_attr @ w_rad).reshape(E, 5, C)
    f0 = x0[src]
    f1 = x1[src]
    Y1 = rhat
    p00_0 = f0 * R[:, 0, :]
    p11_0 = torch.einsum('ejc,ej->ec', f1, Y1) * R[:, 1, :]
    p01_1 = torch.einsum('ec,ej->ejc', f0, Y1) * R[:, 2, :][:, None, :]
    p10_1 = f1 * R[:, 3, :][:, None, :]
    p11_1 = torch.einsum('ijk,ekc,ej->eic', cg_eps, f1, Y1) * R[:, 4, :][:, None, :]
    m0 = torch.concatenate([p00_0, p11_0], axis=-1) @ w_si0
    m1 = torch.einsum('ejp,pc->ejc', torch.concatenate([p01_1, p10_1, p11_1], axis=-1), w_si1)
    agg0 = _segment_sum(m0, dst, N)
    agg1 = _segment_sum(m1.reshape(E, 3 * C), dst, N).reshape(N, 3, C)
    gate = _sigmoid(agg0)
    out1 = agg1 * gate[:, None, :]
    return torch.concatenate([agg0, out1.reshape(N, 3 * C)], axis=-1)
```

```cpp
#include <cuda_runtime.h>
#include <cuda_bf16.h>
#include <stdint.h>
#include <stdio.h>
#include <type_traits>

namespace eqf {

constexpr int NN = 25000;
constexpr int NE = 800000;
constexpr int NB = 132;
constexpr int NPB = 190;
constexpr int CH = 6064;
constexpr int HA = 96;
constexpr int NH = 2 * NB;
constexpr int CAPH = 3296;
constexpr int SLOTS = CAPH + 8;
#define EQF_GW 12
#define EQF_NBUF 2
#define EQF_RING 3
#define EQF_REG_G 112
#define EQF_REG_E 176
constexpr int GW = EQF_GW;
constexpr int NST = EQF_NBUF;
constexpr int NT = (GW + 4) * 32;
constexpr int RING = EQF_RING;
constexpr int LBO_S = 144;
constexpr int ATOM = 1184;
constexpr int TILE = 16 * ATOM;
constexpr int OROW = 528;
constexpr int R1 = (CH / 4 + NT - 1) / NT;
constexpr int NTG = GW * 32;
constexpr int R2A = (CAPH + NTG - 1) / NTG;
constexpr int R2B = (CAPH + 127) / 128;
constexpr int HB = 272;

constexpr int OFF_SC = 0;
constexpr int OFF_SS = OFF_SC + 2 * SLOTS * 8;
constexpr int OFF_X = (OFF_SS + 2 * SLOTS * 2 + 127) / 128 * 128;
constexpr int OFF_S = OFF_X + GW * NST * 4096;
constexpr int OFF_OUT = OFF_S + RING * TILE;
constexpr int OFF_OFFS = OFF_OUT + 2 * 8 * OROW;
constexpr int OFF_EPS = OFF_OFFS + 200 * 4;
constexpr int OFF_BAR = OFF_EPS + 128;
constexpr int OFF_MISC = OFF_BAR + 128;
constexpr int SMEM_BYTES = OFF_MISC + 64;
constexpr int OFF_HIST = OFF_OUT;
constexpr int OFF_LOFF = OFF_HIST + HB * 4;
constexpr int OFF_DELTA = OFF_LOFF + HB * 4;
constexpr int OFF_HIST2 = OFF_DELTA + HB * 4;
static_assert(OFF_HIST2 + 2 * 104 * 4 <= OFF_OFFS, "hist alias");
constexpr int OFF_STAGE = OFF_X;
constexpr int OFF_RD = 0;
constexpr int OFF_RS = OFF_RD + CH * 4;
constexpr int OFF_RA = OFF_RS + CH * 4;
constexpr int OFF_RY = OFF_S;
static_assert(OFF_STAGE + CH * 16 <= OFF_S && OFF_RA + CH * 2 <= OFF_X && OFF_RY + CH * 6 <= OFF_OUT, "phase 1 alias");
static_assert(OFF_RA % 16 == 0 && OFF_RY % 16 == 0 && OFF_STAGE % 16 == 0, "align");
static_assert(NT >= 128 + NH, "phase 1 roles");
static_assert(OFF_S % 16 == 0 && OFF_OUT % 16 == 0 && OFF_BAR % 8 == 0 && OFF_EPS % 16 == 0, "align");
static_assert(SMEM_BYTES <= 232448, "smem");
static_assert((long long)NB * CH >= NE && NB * NPB >= NN, "cover");
static_assert((2 * RING + 1 + R1 + 5) * 8 <= 128, "bars");
static_assert(CAPH * 16 <= RING * TILE, "half B staging");
static_assert(HA % 8 == 0 && NPB - HA <= 96 && 2 * SLOTS < 65536, "halves");

__device__ uint4 g_rec[(size_t)NH * CAPH];
__device__ unsigned int g_cnt[NH];
__device__ uint4 g_wfrag[20 * 128];
__device__ unsigned long long g_bar[2 * 16];
#define TS(i)
#define TSW(i)

__device__ __forceinline__ uint32_t smem_u32(const void* p) { return (uint32_t)__cvta_generic_to_shared(p); }

__device__ __forceinline__ int4 ldg_stream_i4(const void* p, uint64_t pol) {
  int4 v;
  asm volatile("ld.global.nc.L1::no_allocate.L2::cache_hint.v4.s32 {%0,%1,%2,%3}, [%4], %5;"
               : "=r"(v.x), "=r"(v.y), "=r"(v.z), "=r"(v.w) : "l"(p), "l"(pol));
  return v;
}
__device__ __forceinline__ uint2 ldg_stream_u2(const void* p, uint64_t pol) {
  uint2 v;
  asm volatile("ld.global.nc.L2::cache_hint.v2.u32 {%0,%1}, [%2], %3;" : "=r"(v.x), "=r"(v.y) : "l"(p), "l"(pol));
  return v;
}
__device__ __forceinline__ uint4 ldg_cg_u4(const void* p, uint64_t pol) {
  uint4 v;
  asm volatile("ld.global.cg.L2::cache_hint.v4.u32 {%0,%1,%2,%3}, [%4], %5;"
               : "=r"(v.x), "=r"(v.y), "=r"(v.z), "=r"(v.w) : "l"(p), "l"(pol) : "memory");
  return v;
}
__device__ __forceinline__ uint4 ldg_x(const void* p) {
  uint4 v;
  asm volatile("ld.global.nc.v4.u32 {%0,%1,%2,%3}, [%4];" : "=r"(v.x), "=r"(v.y), "=r"(v.z), "=r"(v.w) : "l"(p));
  return v;
}
__device__ __forceinline__ void mbar_init(uint32_t bar, uint32_t cnt) {
  asm volatile("mbarrier.init.shared::cta.b64 [%0], %1;" ::"r"(bar), "r"(cnt) : "memory");
}
__device__ __forceinline__ void mbar_arrive(uint32_t bar) {
  asm volatile("mbarrier.arrive.shared::cta.b64 _, [%0];" ::"r"(bar) : "memory");
}
__device__ __forceinline__ void mbar_arrive_lane0(uint32_t bar, int lane) {
  asm volatile("{\n.reg .pred p;\nsetp.eq.s32 p, %1, 0;\n@p mbarrier.arrive.shared::cta.b64 _, [%0];\n}" ::"r"(bar), "r"(lane) : "memory");
}
__device__ __forceinline__ void mbar_wait(uint32_t bar, uint32_t parity) {
  uint32_t done;
  int it = 0;
  do {
    asm volatile("{\n.reg .pred p;\nmbarrier.try_wait.parity.shared::cta.b64 p, [%1], %2;\nselp.u32 %0, 1, 0, p;\n}"
                 : "=r"(done) : "r"(bar), "r"(parity) : "memory");
  } while (!done && ++it < (1 << 22));
}
__device__ __forceinline__ void bulk_load(uint32_t dst, const void* src, uint32_t bytes, uint32_t bar, uint64_t pol,
                                          uint32_t expect) {
  if (expect) asm volatile("mbarrier.arrive.expect_tx.shared::cta.b64 _, [%0], %1;" ::"r"(bar), "r"(expect) : "memory");
  asm volatile("cp.async.bulk.shared::cluster.global.mbarrier::complete_tx::bytes.L2::cache_hint [%0], [%1], %2, [%3], %4;"
               ::"r"(dst), "l"(src), "r"(bytes), "r"(bar), "l"(pol) : "memory");
}
__device__ __forceinline__ void fence_async_smem() { asm volatile("fence.proxy.async.shared::cta;" ::: "memory"); }
__device__ __forceinline__ uint32_t pack_bf16(float lo, float hi) {
  uint32_t r;
  asm("cvt.rn.bf16x2.f32 %0, %1, %2;" : "=r"(r) : "f"(hi), "f"(lo));
  return r;
}
__device__ __forceinline__ float bf_lo(uint32_t v) { return __uint_as_float(v << 16); }
__device__ __forceinline__ float bf_hi(uint32_t v) { return __uint_as_float(v & 0xffff0000u); }

__device__ __forceinline__ uint32_t movm(uint32_t a) {
  uint32_t d;
  asm volatile("movmatrix.sync.aligned.m8n8.trans.b16 %0, %1;" : "=r"(d) : "r"(a));
  return d;
}
__device__ __forceinline__ void mma16808(float* c, uint32_t a0, uint32_t a1, uint32_t b) {
  asm volatile("mma.sync.aligned.m16n8k8.row.col.f32.bf16.bf16.f32 {%0,%1,%2,%3}, {%4,%5}, {%6}, {%0,%1,%2,%3};"
               : "+f"(c[0]), "+f"(c[1]), "+f"(c[2]), "+f"(c[3]) : "r"(a0), "r"(a1), "r"(b));
}

__device__ __forceinline__ uint64_t make_desc(uint32_t addr, uint32_t lbo, uint32_t sbo) {
  return (uint64_t)((addr & 0x3FFFF) >> 4) | ((uint64_t)(lbo >> 4) << 16) | ((uint64_t)(sbo >> 4) << 32);
}
__device__ __forceinline__ void wgmma_n8(float* d, const uint32_t* a, uint64_t db, int scale_d) {
  asm volatile(
      "{\n.reg .pred p;\nsetp.ne.b32 p, %9, 0;\n"
      "wgmma.mma_async.sync.aligned.m64n8k16.f32.bf16.bf16 {%0,%1,%2,%3}, {%4,%5,%6,%7}, %8, p, 1, 1, 0;\n}"
      : "+f"(d[0]), "+f"(d[1]), "+f"(d[2]), "+f"(d[3])
      : "r"(a[0]), "r"(a[1]), "r"(a[2]), "r"(a[3]), "l"(db), "r"(scale_d));
}
__device__ __forceinline__ void wgmma_n24(float* d, const uint32_t* a, uint64_t db, int scale_d) {
  asm volatile(
      "{\n.reg .pred p;\nsetp.ne.b32 p, %17, 0;\n"
      "wgmma.mma_async.sync.aligned.m64n24k16.f32.bf16.bf16 {%0,%1,%2,%3,%4,%5,%6,%7,%8,%9,%10,%11}, {%12,%13,%14,%15}, %16, p, 1, 1, 0;\n}"
      : "+f"(d[0]), "+f"(d[1]), "+f"(d[2]), "+f"(d[3]), "+f"(d[4]), "+f"(d[5]), "+f"(d[6]), "+f"(d[7]),
        "+f"(d[8]), "+f"(d[9]), "+f"(d[10]), "+f"(d[11])
      : "r"(a[0]), "r"(a[1]), "r"(a[2]), "r"(a[3]), "l"(db), "r"(scale_d));
}
__device__ __forceinline__ void wgmma_n72(float* d, const uint32_t* a, uint64_t db, int scale_d) {
  asm volatile(
      "{\n.reg .pred p;\nsetp.ne.b32 p, %41, 0;\n"
      "wgmma.mma_async.sync.aligned.m64n72k16.f32.bf16.bf16 "
      "{%0,%1,%2,%3,%4,%5,%6,%7,%8,%9,%10,%11,%12,%13,%14,%15,%16,%17,"
      "%18,%19,%20,%21,%22,%23,%24,%25,%26,%27,%28,%29,%30,%31,%32,%33,%34,%35}, {%36,%37,%38,%39}, %40, p, 1, 1, 0;\n}"
      : "+f"(d[0]), "+f"(d[1]), "+f"(d[2]), "+f"(d[3]), "+f"(d[4]), "+f"(d[5]), "+f"(d[6]), "+f"(d[7]),
        "+f"(d[8]), "+f"(d[9]), "+f"(d[10]), "+f"(d[11]), "+f"(d[12]), "+f"(d[13]), "+f"(d[14]), "+f"(d[15]),
        "+f"(d[16]), "+f"(d[17]), "+f"(d[18]), "+f"(d[19]), "+f"(d[20]), "+f"(d[21]), "+f"(d[22]), "+f"(d[23]),
        "+f"(d[24]), "+f"(d[25]), "+f"(d[26]), "+f"(d[27]), "+f"(d[28]), "+f"(d[29]), "+f"(d[30]), "+f"(d[31]),
        "+f"(d[32]), "+f"(d[33]), "+f"(d[34]), "+f"(d[35])
      : "r"(a[0]), "r"(a[1]), "r"(a[2]), "r"(a[3]), "l"(db), "r"(scale_d));
}

struct Params {
  const __nv_bfloat16* x;
  const __nv_bfloat16* rhat;
  const __nv_bfloat16* eattr;
  const int* src;
  const int* dst;
  const __nv_bfloat16* wrad;
  const __nv_bfloat16* w0;
  const __nv_bfloat16* w1;
  const __nv_bfloat16* eps;
  __nv_bfloat16* out;
};

__device__ __noinline__ void slow_path(const Params& p, unsigned char* smem, int bin) {
  const int warp = threadIdx.x >> 5, lane = threadIdx.x & 31;
  float* S = reinterpret_cast<float*>(smem) + warp * 1024;
  float* P = reinterpret_cast<float*>(smem) + (NT / 32) * 1024 + warp * 768;
  const int n0 = bin * NPB, n1 = min(n0 + NPB, NN);
  for (int n = n0 + warp; n < n1; n += NT / 32) {
    float acc[4][8];
#pragma unroll
    for (int j = 0; j < 4; j++)
#pragma unroll
      for (int c = 0; c < 8; c++) acc[j][c] = 0.f;
    for (int e0 = 0; e0 < NE; e0 += 32) {
      const int e = e0 + lane;
      const bool m = (e < NE) && (p.dst[e] == n);
      unsigned bal = __ballot_sync(0xffffffffu, m);
      while (bal) {
        const int l = __ffs(bal) - 1;
        bal &= bal - 1;
        const int ee = e0 + l;
        const float a = __bfloat162float(p.eattr[ee]);
        const float cf[4] = {a, a * __bfloat162float(p.rhat[ee * 3]), a * __bfloat162float(p.rhat[ee * 3 + 1]),
                             a * __bfloat162float(p.rhat[ee * 3 + 2])};
        const uint4 v = *reinterpret_cast<const uint4*>(p.x + (size_t)p.src[ee] * 256 + lane * 8);
        const uint32_t w[4] = {v.x, v.y, v.z, v.w};
#pragma unroll
        for (int c = 0; c < 4; c++) {
#pragma unroll
          for (int j = 0; j < 4; j++) {
            acc[j][2 * c] += cf[j] * bf_lo(w[c]);
            acc[j][2 * c + 1] += cf[j] * bf_hi(w[c]);
          }
        }
      }
    }
#pragma unroll
    for (int j = 0; j < 4; j++)
#pragma unroll
      for (int c = 0; c < 8; c++) S[j * 256 + lane * 8 + c] = acc[j][c];
    __syncwarp();
    for (int c = lane; c < 64; c += 32) {
      float wr[5];
      for (int k = 0; k < 5; k++) wr[k] = __bfloat162float(p.wrad[k * 64 + c]);
      P[c] = wr[0] * S[c];
      P[64 + c] = wr[1] * (S[256 + 64 + c] + S[512 + 128 + c] + S[768 + 192 + c]);
      for (int i = 0; i < 3; i++) {
        P[128 + i * 192 + c] = wr[2] * S[(1 + i) * 256 + c];
        P[128 + i * 192 + 64 + c] = wr[3] * S[(1 + i) * 64 + c];
        float t = 0.f;
        for (int j = 0; j < 3; j++)
          for (int k = 0; k < 3; k++)
            t += __bfloat162float(p.eps[i * 9 + j * 3 + k]) * S[(1 + j) * 256 + (1 + k) * 64 + c];
        P[128 + i * 192 + 128 + c] = wr[4] * t;
      }
    }
    __syncwarp();
    for (int c = lane; c < 64; c += 32) {
      float a0 = 0.f, a1[3] = {0.f, 0.f, 0.f};
      for (int k = 0; k < 128; k++) a0 += P[k] * __bfloat162float(p.w0[k * 64 + c]);
      for (int k = 0; k < 192; k++) {
        const float w = __bfloat162float(p.w1[k * 64 + c]);
        for (int i = 0; i < 3; i++) a1[i] += P[128 + i * 192 + k] * w;
      }
      const float gate = 1.f / (1.f + __expf(-a0));
      p.out[(size_t)n * 256 + c] = __float2bfloat16(a0);
      for (int i = 0; i < 3; i++) p.out[(size_t)n * 256 + 64 + i * 64 + c] = __float2bfloat16(a1[i] * gate);
    }
    __syncwarp();
  }
}

#define EQF_EARLY 1

#define EQF_DELAY 0

#define EQF_BW 8

#define EQF_PREF 0
#define EQF_PREF_PCT 100

struct Stage {
  uint32_t b1, b2;
  int meta;
};

__global__ void __launch_bounds__(NT, 1) eqf_kernel(const __grid_constant__ Params p) {
  extern __shared__ __align__(128) unsigned char smem[];
  const int tid = threadIdx.x, warp = tid >> 5, lane = tid & 31;
  const int bin = blockIdx.x;
  uint4* stage = reinterpret_cast<uint4*>(smem + OFF_STAGE);
  uint32_t* offs = reinterpret_cast<uint32_t*>(smem + OFF_OFFS);
  uint32_t* hist = reinterpret_cast<uint32_t*>(smem + OFF_HIST);
  uint32_t* hist2 = reinterpret_cast<uint32_t*>(smem + OFF_HIST2);
  uint32_t* loff = reinterpret_cast<uint32_t*>(smem + OFF_LOFF);
  uint32_t* delta = reinterpret_cast<uint32_t*>(smem + OFF_DELTA);
  volatile uint32_t* misc = reinterpret_cast<volatile uint32_t*>(smem + OFF_MISC);
  uint2* sc = reinterpret_cast<uint2*>(smem + OFF_SC);
  uint16_t* ss = reinterpret_cast<uint16_t*>(smem + OFF_SS);
  const uint32_t sbase = smem_u32(smem);
  const uint32_t bar_full = sbase + OFF_BAR, bar_empty = bar_full + 8 * RING;
  const uint32_t bar_in = bar_empty + 8 * RING;
  const uint32_t bar_cnt = bar_in + 8 * (1 + R1);
  const uint32_t bar_stg = bar_cnt + 8;
  const uint32_t bar_b = bar_stg + 8;
  const uint32_t bar_a1 = bar_b + 8;

  TS(0);
  uint64_t pol_stream;
  asm volatile("createpolicy.fractional.L2::evict_first.b64 %0, 1.0;" : "=l"(pol_stream));

  const int e0 = bin * CH;
  const int nE = min(CH, NE - e0);
  unsigned long long bar_target = 0;
  auto load_payload = [&](const int r) {
    const int nr = min(NT * 4, nE - r * NT * 4);
    if (nr > 0) {
      const int o = r * NT * 4;
      bulk_load(sbase + OFF_RS + o * 4, p.src + e0 + o, nr * 4, bar_in + 8 * (1 + r), pol_stream, nr * 12);
      bulk_load(sbase + OFF_RA + o * 2, p.eattr + e0 + o, nr * 2, bar_in + 8 * (1 + r), pol_stream, 0);
      bulk_load(sbase + OFF_RY + o * 6, p.rhat + (size_t)(e0 + o) * 3, nr * 6, bar_in + 8 * (1 + r), pol_stream, 0);
    }
  };
  if (tid == 0) {
    for (int s = 0; s < RING; s++) {
      mbar_init(bar_full + 8 * s, 8);
      mbar_init(bar_empty + 8 * s, 4);
    }
    for (int s = 0; s <= R1; s++) mbar_init(bar_in + 8 * s, 1);
    mbar_init(bar_cnt, 1);
    mbar_init(bar_stg, EQF_BW);
    mbar_init(bar_b, 4);
    mbar_init(bar_a1, 1);
    asm volatile("fence.mbarrier_init.release.cluster;" ::: "memory");
    fence_async_smem();
    bulk_load(sbase + OFF_RD, p.dst + e0, nE * 4, bar_in, pol_stream, nE * 4);
#pragma unroll
    for (int r = 0; r < EQF_EARLY; r++) load_payload(r);
    misc[2] = 0;
  }
  if (tid == 0 || tid == NTG) {
    unsigned long long v0;
    asm volatile("ld.relaxed.gpu.global.u64 %0, [%1];" : "=l"(v0) : "l"(&g_bar[tid == 0 ? 0 : 16]) : "memory");
    bar_target = (v0 / NB + 1) * NB;
  }
  if (tid < HB) hist[tid] = 0;
  if (tid < 208) hist2[tid] = 0;
  const int wfw = bin * 78 + tid - (NT - 96);
  const bool wf_on = (tid >= NT - 96) && (tid - (NT - 96) < 78) && (wfw < 10240);
  unsigned short wf0 = 0, wf1 = 0, wf2 = 0, wf3 = 0;
  if (wf_on) {
    const int r = wfw & 3, et = (wfw >> 2) & 127, ks = (wfw >> 9) & 3, mat = wfw >> 11;
    const int m = (et >> 5) * 16 + ((et & 31) >> 2) + (r & 1) * 8;
    const int pk = ks * 16 + (r >> 1) * 8 + 2 * (et & 3);
    const int ch0 = 8 * (pk & 7) + (pk >> 3), ch1 = ch0 + 8;
    const unsigned short* W = reinterpret_cast<const unsigned short*>(mat < 2 ? p.w0 + mat * 4096 : p.w1 + (mat - 2) * 4096);
    const unsigned short* wr = reinterpret_cast<const unsigned short*>(p.wrad) + mat * 64;
    wf0 = __ldg(W + ch0 * 64 + m); wf1 = __ldg(wr + ch0);
    wf2 = __ldg(W + ch1 * 64 + m); wf3 = __ldg(wr + ch1);
  }
  __syncthreads();
  mbar_wait(bar_in, 0);
  if (tid == 0) {
#pragma unroll
    for (int r = EQF_EARLY; r < R1; r++) load_payload(r);
  }
  uint32_t key[R1 * 4];
#pragma unroll
  for (int r = 0; r < R1; r++) {
    const int q = min((tid + r * NT) * 4, nE - 4);
    const int4 dv = *reinterpret_cast<const int4*>(smem + OFF_RD + q * 4);
    const bool act = (tid + r * NT) * 4 < nE;
    const int d4[4] = {dv.x, dv.y, dv.z, dv.w};
#pragma unroll
    for (int i = 0; i < 4; i++) {
      const uint32_t b0 = (uint32_t)d4[i] / NPB;
      const uint32_t dl = (uint32_t)d4[i] - b0 * NPB;
      const uint32_t b = act ? (dl >= (uint32_t)HA ? b0 + NB : b0) : (uint32_t)NH;
      const uint32_t rank = atomicAdd(&hist[b], 1u);
      key[r * 4 + i] = (b << 21) | (dl << 13) | rank;
    }
  }
  __syncthreads();
  TS(1);
  uint32_t my_cnt = 0, my_g = 0;
  if (warp == 0) {
    uint32_t c[9], s = 0;
#pragma unroll
    for (int j = 0; j < 9; j++) {
      const int b = lane * 9 + j;
      c[j] = (b < NH) ? hist[b] : 0;
      s += c[j];
    }
    uint32_t incl = s;
#pragma unroll
    for (int o = 1; o < 32; o <<= 1) {
      const uint32_t t = __shfl_up_sync(0xffffffffu, incl, o);
      if (lane >= o) incl += t;
    }
    uint32_t ex = incl - s;
#pragma unroll
    for (int j = 0; j < 9; j++) {
      const int b = lane * 9 + j;
      if (b <= NH) loff[b] = ex;
      ex += c[j];
    }
  } else if (tid >= 128 && tid - 128 < NH) {
    my_cnt = hist[tid - 128];
    my_g = atomicAdd(&g_cnt[tid - 128], my_cnt);
  }
  __syncthreads();
#pragma unroll
  for (int r = 0; r < R1; r++) {
    const int q = min((tid + r * NT) * 4, nE - 4);
    if (r * NT * 4 < nE) mbar_wait(bar_in + 8 * (1 + r), 0);
    const uint4 sv = *reinterpret_cast<const uint4*>(smem + OFF_RS + q * 4);
    const uint2 av = *reinterpret_cast<const uint2*>(smem + OFF_RA + q * 2);
    const uint2 y0 = *reinterpret_cast<const uint2*>(smem + OFF_RY + q * 6);
    const uint2 y1 = *reinterpret_cast<const uint2*>(smem + OFF_RY + q * 6 + 8);
    const uint2 y2 = *reinterpret_cast<const uint2*>(smem + OFF_RY + q * 6 + 16);
    const uint32_t s4[4] = {sv.x, sv.y, sv.z, sv.w};
    const float a4[4] = {bf_lo(av.x), bf_hi(av.x), bf_lo(av.y), bf_hi(av.y)};
    const uint32_t w[6] = {y0.x, y0.y, y1.x, y1.y, y2.x, y2.y};
#pragma unroll
    for (int i = 0; i < 4; i++) {
      const uint32_t k = key[r * 4 + i];
      float y[3];
#pragma unroll
      for (int j = 0; j < 3; j++) {
        const int h = i * 3 + j;
        y[j] = (h & 1) ? bf_hi(w[h >> 1]) : bf_lo(w[h >> 1]);
      }
      uint4 rec;
      rec.x = pack_bf16(a4[i], a4[i] * y[0]);
      rec.y = pack_bf16(a4[i] * y[1], a4[i] * y[2]);
      rec.z = s4[i] | (((k >> 13) & 0xffu) << 16);
      rec.w = k >> 21;
      if (rec.w < (uint32_t)NH) stage[loff[rec.w] + (k & 0x1fffu)] = rec;
    }
  }
  if (tid >= 128 && tid - 128 < NH) {
    const int b = tid - 128;
    delta[b] = (my_g + my_cnt <= (uint32_t)CAPH) ? (uint32_t)(b * CAPH) + my_g - loff[b] : 0xffffffffu;
  }
  if (wf_on) {
    const float v0 = __uint_as_float((uint32_t)wf0 << 16) * __uint_as_float((uint32_t)wf1 << 16);
    const float v1 = __uint_as_float((uint32_t)wf2 << 16) * __uint_as_float((uint32_t)wf3 << 16);
    reinterpret_cast<uint32_t*>(g_wfrag)[wfw] = pack_bf16(v0, v1);
  }
  __syncthreads();
  TS(2);
  if (EQF_PREF == 4 && tid == 32) {
    const int r0 = bin * NPB, r1 = min(r0 + NPB, NN);
    const int bytes = ((r1 - r0) * 512 * EQF_PREF_PCT / 100) & ~15;
    asm volatile("cp.async.bulk.prefetch.L2.global [%0], %1;"
                 ::"l"(reinterpret_cast<const char*>(p.x) + (size_t)r0 * 512), "r"(bytes) : "memory");
  }
  const int nA = (int)loff[NB];
  auto write_out = [&](const int i) {
    const uint4 rec = stage[i];
    const uint32_t d = delta[rec.w];
    if (d != 0xffffffffu) {
      asm volatile("st.global.v4.u32 [%0], {%1,%2,%3,%4};"
                   ::"l"(g_rec + (d + i)), "r"(rec.x), "r"(rec.y), "r"(rec.z), "r"(rec.w) : "memory");
    }
  };
  for (int i = tid; i < nA; i += NT) write_out(i);
  __syncthreads();
  TS(3);

  const int n0 = bin * NPB;
  const int nn = min(NPB, NN - n0);
  const int nn8 = (nn + 7) & ~7;
  uint32_t cntA = 0, cntB = 0;

  auto sort_half = [&](auto Rc, auto NTHc, const int bid, const int t0, const int half, const uint32_t cnt,
                       const uint32_t* rx, const uint32_t* ry, const uint32_t* rz, auto after_hist) {
    constexpr int R = decltype(Rc)::value, NTH = decltype(NTHc)::value;
    uint32_t* h2 = hist2 + half * 104;
    const uint32_t nb0 = half * HA;
    uint32_t rk[R];
#pragma unroll
    for (int r = 0; r < R; r++) {
      const uint32_t i = t0 + r * NTH;
      const uint32_t dl = (i < cnt) ? (rz[r] >> 16) - nb0 : 100u;
      rk[r] = atomicAdd(&h2[dl], 1u);
    }
    after_hist();
    asm volatile("bar.sync %0, %1;" ::"r"(bid), "n"(NTH) : "memory");
    if (t0 < 32) {
      uint32_t c[3], s = 0;
#pragma unroll
      for (int j = 0; j < 3; j++) {
        c[j] = h2[t0 * 3 + j];
        s += c[j];
      }
      uint32_t incl = s;
#pragma unroll
      for (int o = 1; o < 32; o <<= 1) {
        const uint32_t t = __shfl_up_sync(0xffffffffu, incl, o);
        if (t0 >= o) incl += t;
      }
      uint32_t ex = incl - s + half * SLOTS;
#pragma unroll
      for (int j = 0; j < 3; j++) {
        offs[nb0 + t0 * 3 + j] = ex | ((ex + c[j]) << 16);
        ex += c[j];
      }
    }
    if (t0 >= 32 && t0 < 40) {
      sc[half * SLOTS + cnt + (t0 - 32)] = make_uint2(0u, 0u);
      ss[half * SLOTS + cnt + (t0 - 32)] = 0;
    }
    asm volatile("bar.sync %0, %1;" ::"r"(bid), "n"(NTH) : "memory");
#pragma unroll
    for (int r = 0; r < R; r++) {
      const uint32_t i = t0 + r * NTH;
      if (i < cnt) {
        const uint32_t pp = (offs[rz[r] >> 16] & 0xffffu) + rk[r];
        sc[pp] = make_uint2(rx[r], ry[r]);
        ss[pp] = (uint16_t)rz[r];
      }
    }
  };

  auto prefetch_x = [&]() {
    const int r0 = bin * NPB, r1 = min(r0 + NPB, NN);
    const int bytes = ((r1 - r0) * 512 * EQF_PREF_PCT / 100) & ~15;
    asm volatile("cp.async.bulk.prefetch.L2.global [%0], %1;"
                 ::"l"(reinterpret_cast<const char*>(p.x) + (size_t)r0 * 512), "r"(bytes) : "memory");
  };
  if (EQF_PREF == 1 && tid == 32) prefetch_x();
  if (tid == 0) {
    asm volatile("red.release.gpu.global.add.u64 [%0], 1;" ::"l"(&g_bar[0]) : "memory");
    mbar_arrive(bar_a1);
    TS(6);
  }
  if (tid >= NT - EQF_BW * 32) {
    mbar_wait(bar_a1, 0);
    for (int i = nA + tid - (NT - EQF_BW * 32); i < nE; i += EQF_BW * 32) write_out(i);
    __syncwarp();
    mbar_arrive_lane0(bar_stg, lane);
    if (warp < GW) asm volatile("bar.arrive 3, %0;" ::"n"(EQF_BW * 32) : "memory");
  }

  if (warp < GW) {
    if (tid == 0) {
      unsigned long long v;
      int it = 0;
      do {
        asm volatile("ld.acquire.gpu.global.u64 %0, [%1];" : "=l"(v) : "l"(&g_bar[0]) : "memory");
      } while (v < bar_target && ++it < (1 << 22));
    }
    asm volatile("bar.sync 2, %0;" ::"n"(NTG) : "memory");
    TS(4);
    if (EQF_PREF == 2 && tid == 32) prefetch_x();
    uint32_t rx[R2A], ry[R2A], rz[R2A];
#pragma unroll
    for (int r = 0; r < R2A; r++) {
      const uint32_t i = min(tid + r * NTG, CAPH - 1);
      const uint4 v = ldg_cg_u4(g_rec + (size_t)bin * CAPH + i, pol_stream);
      rx[r] = v.x; ry[r] = v.y; rz[r] = v.z;
    }
    if (tid == 0) {
      uint32_t ca, cb;
      asm volatile("ld.relaxed.gpu.global.u32 %0, [%1];" : "=r"(ca) : "l"(&g_cnt[bin]) : "memory");
      asm volatile("ld.relaxed.gpu.global.u32 %0, [%1];" : "=r"(cb) : "l"(&g_cnt[NB + bin]) : "memory");
      misc[0] = ca;
      misc[1] = cb;
      g_cnt[bin] = 0;
      g_cnt[NB + bin] = 0;
      mbar_arrive(bar_cnt);
    }
    asm volatile("bar.sync 2, %0;" ::"n"(NTG) : "memory");
    if (EQF_PREF == 3 && tid == 32) prefetch_x();
    cntA = misc[0];
    cntB = misc[1];
    if (cntA <= (uint32_t)CAPH && cntB <= (uint32_t)CAPH) {
      sort_half(std::integral_constant<int, R2A>{}, std::integral_constant<int, NTG>{}, 2, tid, 0, cntA, rx, ry, rz, []() {});
      asm volatile("bar.sync 2, %0;" ::"n"(NTG) : "memory");
    }
    mbar_wait(bar_stg, 0);
    TS(5);
  } else {
    const int et = tid - NTG;
    asm volatile("bar.sync 3, %0;" ::"n"(EQF_BW * 32) : "memory");
    if (et == 0) {
      TSW(9);
      asm volatile("red.release.gpu.global.add.u64 [%0], 1;" ::"l"(&g_bar[16]) : "memory");
      TSW(10);
      unsigned long long v;
      int it = 0;
      do {
        asm volatile("ld.acquire.gpu.global.u64 %0, [%1];" : "=l"(v) : "l"(&g_bar[16]) : "memory");
      } while (v < bar_target && ++it < (1 << 22));
    }
    asm volatile("bar.sync 1, 128;" ::: "memory");
    if (et == 0) TSW(11);
    uint32_t rx[R2B], ry[R2B], rz[R2B];
#pragma unroll
    for (int r = 0; r < R2B; r++) {
      const uint32_t i = min(et + r * 128, CAPH - 1);
      const uint4 v = ldg_cg_u4(g_rec + (size_t)(NB + bin) * CAPH + i, pol_stream);
      rx[r] = v.x; ry[r] = v.y; rz[r] = v.z;
    }
    mbar_wait(bar_cnt, 0);
    cntA = misc[0];
    cntB = misc[1];
    if (cntA <= (uint32_t)CAPH && cntB <= (uint32_t)CAPH) {
      sort_half(std::integral_constant<int, R2B>{}, std::integral_constant<int, 128>{}, 1, et, 1, cntB, rx, ry, rz, []() {});
      __syncwarp();
      mbar_arrive_lane0(bar_b, lane);
    }
    if (et == 0) TSW(13);
  }
  if (cntA > (uint32_t)CAPH || cntB > (uint32_t)CAPH) {
    mbar_wait(bar_stg, 0);
    slow_path(p, smem, bin);
    return;
  }

  if (warp < GW) {
    asm volatile("setmaxnreg.dec.sync.aligned.u32 %0;" ::"n"(EQF_REG_G));
    const int g = lane >> 2, t = lane & 3, q = lane >> 3;
    const char* xq = reinterpret_cast<const char*>(p.x) + (lane & 7) * 16;
    const uint32_t xs = sbase + OFF_X + warp * NST * 4096;
    const uint32_t cd0 = xs + q * 512 + (((lane & 7) ^ q) * 16);
    const uint32_t cd1 = xs + (4 + q) * 512 + (((lane & 7) ^ (4 + q)) * 16);
    const uint32_t la0 = xs + (lane & 7) * 512 + ((q ^ (lane & 7)) * 16);
    const uint32_t la1 = xs + (lane & 7) * 512 + (((4 + q) ^ (lane & 7)) * 16);
    const uint32_t sc_s = sbase + OFF_SC + t * 16 + (g & 3) * 2;
    const uint32_t ss_s = sbase + OFF_SS + q * 2;
    const uint32_t mask1 = (g < 4) ? 0xffffffffu : 0u;
    uint32_t st[4];
#pragma unroll
    for (int c = 0; c < 4; c++) {
      const int blk = 2 * (c >> 1) + (t >> 1), jj = 2 * (t & 1) + (c & 1);
      const int a = (blk == 0) ? (jj == 0 ? 15 : 11 + jj) : (jj == 0 ? 8 + blk : 3 * (jj - 1) + (blk - 1));
      st[c] = sbase + OFF_S + a * ATOM + g * LBO_S;
    }
    float acc[8][4];
#pragma unroll
    for (int i = 0; i < 8; i++) acc[i][0] = acc[i][1] = acc[i][2] = acc[i][3] = 0.f;

    int node, pos, end;
    bool b_ready = false;
    auto next_node = [&]() {
      int n = 0;
      if (lane == 0) n = (int)atomicAdd(const_cast<uint32_t*>(&misc[2]), 1u);
      n = __shfl_sync(0xffffffffu, n, 0);
      node = n;
      if (n < nn8) {
        if (n >= HA && !b_ready) {
          mbar_wait(bar_b, 0);
          b_ready = true;
        }
        const uint32_t be = offs[n];
        pos = (int)(be & 0xffffu);
        end = (int)(be >> 16);
      }
    };
    auto issue = [&](Stage& B, const int i) {
      if (node >= nn8) {
        B.meta = -1;
        asm volatile("cp.async.commit_group;" ::: "memory");
        return;
      }
      const int cnt = end - pos;
      const bool last = (cnt <= 8);
      B.meta = node | (last ? 256 : 0);
      uint32_t s0, s1, c0, c1;
      asm volatile("ld.shared.u16 %0, [%1];" : "=r"(s0) : "r"(ss_s + pos * 2));
      asm volatile("ld.shared.u16 %0, [%1+8];" : "=r"(s1) : "r"(ss_s + pos * 2));
      asm volatile("ld.shared.u16 %0, [%1];" : "=r"(c0) : "r"(sc_s + pos * 8));
      asm volatile("ld.shared.u16 %0, [%1+8];" : "=r"(c1) : "r"(sc_s + pos * 8));
      const char* p0 = xq + (size_t)s0 * 512;
      const char* p1 = xq + (size_t)s1 * 512;
      const int z0 = (q < cnt) ? 16 : 0, z1 = (4 + q < cnt) ? 16 : 0;
#pragma unroll
      for (int k = 0; k < 4; k++) {
        asm volatile("cp.async.cg.shared.global [%0], [%1], 16, %2;" ::"r"(cd0 + i * 4096 + k * 128), "l"(p0 + k * 128), "r"(z0) : "memory");
        asm volatile("cp.async.cg.shared.global [%0], [%1], 16, %2;" ::"r"(cd1 + i * 4096 + k * 128), "l"(p1 + k * 128), "r"(z1) : "memory");
      }
      asm volatile("cp.async.commit_group;" ::: "memory");
      const uint32_t m = __funnelshift_lc(0xffffffffu, 0u, (uint32_t)max(16 * min(cnt, 8) - 32 * t, 0));
      const uint32_t b = (c0 | (c1 << 16)) & m;
      B.b1 = b & mask1;
      B.b2 = b & ~mask1;
      pos += 8;
      if (last) next_node();
    };
    auto consume = [&](Stage& B, const int i) {
      asm volatile("cp.async.wait_group %0;" ::"n"(NST - 1) : "memory");
      __syncwarp();
#pragma unroll
      for (int j = 0; j < 8; j++) {
        uint32_t r0, r1, r2, r3;
        asm volatile("ldmatrix.sync.aligned.m8n8.x4.trans.shared.b16 {%0,%1,%2,%3}, [%4];"
                     : "=r"(r0), "=r"(r1), "=r"(r2), "=r"(r3)
                     : "r"(((j & 1) ? la1 : la0) + i * 4096 + (j >> 1) * 128) : "memory");
        const int blk = j >> 1;
        const uint32_t b = (blk & 1) ? B.b2 : B.b1;
        mma16808(acc[(blk >> 1) * 4 + (j & 1) * 2 + 0], r0, r1, b);
        mma16808(acc[(blk >> 1) * 4 + (j & 1) * 2 + 1], r2, r3, b);
      }
      if (B.meta & 256) {
        const int n = B.meta & 255;
        const int tl = n >> 3;
        const int slot = tl % RING;
        mbar_wait(bar_empty + 8 * slot, ((tl / RING) & 1) ^ 1);
        const uint32_t o = slot * TILE + (n & 7) * 16;
#pragma unroll
        for (int c = 0; c < 4; c++) {
          uint32_t w[4];
#pragma unroll
          for (int u = 0; u < 4; u++) {
            const float* a = acc[(c >> 1) * 4 + u];
            w[u] = pack_bf16(a[c & 1], a[2 + (c & 1)]);
          }
          asm volatile("st.shared.v4.u32 [%0], {%1,%2,%3,%4};" ::"r"(st[c] + o), "r"(w[0]), "r"(w[1]), "r"(w[2]), "r"(w[3]) : "memory");
        }
#pragma unroll
        for (int u = 0; u < 8; u++) acc[u][0] = acc[u][1] = acc[u][2] = acc[u][3] = 0.f;
        __syncwarp();
        mbar_arrive_lane0(bar_full + 8 * slot, lane);
      }
      __syncwarp();
    };

    Stage B[NST];
    next_node();
#pragma unroll
    for (int i = 0; i < NST; i++) issue(B[i], i);
    bool run = true;
    while (run) {
#pragma unroll
      for (int i = 0; i < NST; i++) {
        if (B[i].meta < 0) { run = false; break; }
        consume(B[i], i);
        issue(B[i], i);
      }
    }
    TSW(7);
  } else {
    asm volatile("setmaxnreg.inc.sync.aligned.u32 %0;" ::"n"(EQF_REG_E));
    const int et = tid - GW * 32, ew = et >> 5;
    uint32_t wa[5][4][4];
#pragma unroll
    for (int mat = 0; mat < 5; mat++) {
#pragma unroll
      for (int ks = 0; ks < 4; ks++) {
        const uint4 v = __ldcg(&g_wfrag[(mat * 4 + ks) * 128 + et]);
        wa[mat][ks][0] = v.x; wa[mat][ks][1] = v.y; wa[mat][ks][2] = v.z; wa[mat][ks][3] = v.w;
      }
    }
    float* eps = reinterpret_cast<float*>(smem + OFF_EPS);
    if (et < 27) eps[et] = __bfloat162float(p.eps[et]);
    asm volatile("bar.sync 1, 128;" ::: "memory");

    const int ntiles = nn8 >> 3;
    for (int tl = 0; tl < ntiles; tl++) {
      const int slot = tl % RING;
      mbar_wait(bar_full + 8 * slot, (tl / RING) & 1);
      fence_async_smem();
      const uint32_t tb = sbase + OFF_S + slot * TILE;
      float d0[4], d1[12], q[36];
      asm volatile("wgmma.fence.sync.aligned;" ::: "memory");
#pragma unroll
      for (int ks = 0; ks < 4; ks++)
        wgmma_n72(q, wa[4][ks], make_desc(tb + ks * 2 * LBO_S, LBO_S, ATOM), ks);
#pragma unroll
      for (int ks = 0; ks < 4; ks++)
        wgmma_n8(d0, wa[0][ks], make_desc(tb + 15 * ATOM + ks * 2 * LBO_S, LBO_S, ATOM), ks);
#pragma unroll
      for (int j = 0; j < 3; j++)
#pragma unroll
        for (int ks = 0; ks < 4; ks++)
          wgmma_n8(d0, wa[1][ks], make_desc(tb + 4 * j * ATOM + ks * 2 * LBO_S, LBO_S, ATOM), 1);
#pragma unroll
      for (int ks = 0; ks < 4; ks++)
        wgmma_n24(d1, wa[2][ks], make_desc(tb + 12 * ATOM + ks * 2 * LBO_S, LBO_S, ATOM), ks);
#pragma unroll
      for (int ks = 0; ks < 4; ks++)
        wgmma_n24(d1, wa[3][ks], make_desc(tb + 9 * ATOM + ks * 2 * LBO_S, LBO_S, ATOM), 1);
      asm volatile("wgmma.commit_group.sync.aligned;" ::: "memory");
      asm volatile("wgmma.wait_group.sync.aligned 0;" ::: "memory");
      mbar_arrive_lane0(bar_empty + 8 * slot, lane);

      float gate[4];
#pragma unroll
      for (int xx = 0; xx < 4; xx++) gate[xx] = __fdividef(1.f, 1.f + __expf(-d0[xx]));
      uint32_t R[4][2];
      R[0][0] = pack_bf16(d0[0], d0[1]);
      R[0][1] = pack_bf16(d0[2], d0[3]);
#pragma unroll
      for (int i = 0; i < 3; i++) {
        float o[4] = {d1[4 * i], d1[4 * i + 1], d1[4 * i + 2], d1[4 * i + 3]};
#pragma unroll
        for (int m = 0; m < 9; m++) {
          const float e = eps[i * 9 + m];
#pragma unroll
          for (int xx = 0; xx < 4; xx++) o[xx] = fmaf(e, q[4 * m + xx], o[xx]);
        }
        R[1 + i][0] = pack_bf16(o[0] * gate[0], o[1] * gate[1]);
        R[1 + i][1] = pack_bf16(o[2] * gate[2], o[3] * gate[3]);
      }
      const uint32_t ob = sbase + OFF_OUT + (tl & 1) * 8 * OROW;
      {
        const int mi = lane >> 3, j = lane & 7;
        const uint32_t a = ob + j * OROW + ((mi >> 1) * 64 + ew * 16 + (mi & 1) * 8) * 2;
        asm volatile("stmatrix.sync.aligned.m8n8.x4.trans.shared.b16 [%0], {%1,%2,%3,%4};"
                     ::"r"(a), "r"(R[0][0]), "r"(R[0][1]), "r"(R[1][0]), "r"(R[1][1]) : "memory");
        asm volatile("stmatrix.sync.aligned.m8n8.x4.trans.shared.b16 [%0], {%1,%2,%3,%4};"
                     ::"r"(a + 256), "r"(R[2][0]), "r"(R[2][1]), "r"(R[3][0]), "r"(R[3][1]) : "memory");
      }
      asm volatile("bar.sync 1, 128;" ::: "memory");
#pragma unroll
      for (int h = 0; h < 2; h++) {
        const int c = et + 128 * h, row = c >> 5, c16 = c & 31;
        const int nl = tl * 8 + row;
        if (nl < nn) {
          const uint4 v = *reinterpret_cast<const uint4*>(smem + OFF_OUT + (tl & 1) * 8 * OROW + row * OROW + c16 * 16);
          asm volatile("st.global.L2::cache_hint.v4.u32 [%0], {%1,%2,%3,%4}, %5;"
                       ::"l"(reinterpret_cast<char*>(p.out) + (size_t)(n0 + nl) * 512 + c16 * 16),
                         "r"(v.x), "r"(v.y), "r"(v.z), "r"(v.w), "l"(pol_stream) : "memory");
        }
      }
    }
    if (ew == 0) TSW(8);
  }
}

}

extern "C" void kernel_launch(void* const* d_in, const int* in_sizes, int n_in, void* d_out, int out_size) {
  using namespace eqf;
  if (n_in < 9 || in_sizes[0] != NN * 256 || in_sizes[3] != NE || out_size != NN * 256) {
    fprintf(stderr, "kernel_launch: unexpected problem size\n");
    return;
  }
  static bool init = false;
  if (!init) {
    cudaFuncSetAttribute(eqf_kernel, cudaFuncAttributeMaxDynamicSharedMemorySize, SMEM_BYTES);
    init = true;
  }
  Params p;
  p.x = (const __nv_bfloat16*)d_in[0];
  p.rhat = (const __nv_bfloat16*)d_in[1];
  p.eattr = (const __nv_bfloat16*)d_in[2];
  p.src = (const int*)d_in[3];
  p.dst = (const int*)d_in[4];
  p.wrad = (const __nv_bfloat16*)d_in[5];
  p.w0 = (const __nv_bfloat16*)d_in[6];
  p.w1 = (const __nv_bfloat16*)d_in[7];
  p.eps = (const __nv_bfloat16*)d_in[8];
  p.out = (__nv_bfloat16*)d_out;
  eqf_kernel<<<NB, NT, SMEM_BYTES>>>(p);
}
```

```cpp
#include <cuda_runtime.h>
#include <cuda_bf16.h>
#include <stdint.h>
#include <stdio.h>
#include <type_traits>

namespace eqf {

constexpr int NN = 25000;
constexpr int NE = 800000;
constexpr int NB = 132;
constexpr int NPB = 190;
constexpr int CH = 6064;
#define EQF_HA 56
constexpr int HA = EQF_HA;
constexpr int NH = 2 * NB;
constexpr int CAPA = (HA == 96) ? 3360 : (HA == 80) ? 2824 : (HA == 64) ? 2288 : (HA == 56) ? 2016 : 1744;
constexpr int CAPB = (HA == 96) ? 3296 : (HA == 80) ? 3832 : (HA == 64) ? 4368 : (HA == 56) ? 4632 : 4896;
constexpr int SLOTA = CAPA + 8, SLOTB = CAPB + 8;
constexpr int NLA = (HA + 31) / 32, NLB = (192 - HA + 31) / 32;
#define EQF_GW 12
#define EQF_NBUF 2
#define EQF_RING 3
#define EQF_REG_G 112
#define EQF_REG_E 176
constexpr int GW = EQF_GW;
constexpr int NST = EQF_NBUF;
constexpr int NT = (GW + 4) * 32;
constexpr int RING = EQF_RING;
constexpr int LBO_S = 144;
constexpr int ATOM = 1184;
constexpr int TILE = 16 * ATOM;
constexpr int OROW = 528;
constexpr int R1 = (CH / 4 + NT - 1) / NT;
#define EQF_GA 11
constexpr int GA = EQF_GA;
static_assert(GA < GW && GA * NST * 4096 <= 98304, "x ring");
constexpr int NTG = GW * 32;
constexpr int NTM = 256;
constexpr int R2A = (CAPA + NTM - 1) / NTM;
constexpr int R2B = (CAPB + NTM - 1) / NTM;
constexpr int HB = 272;
#define EQF_PT 3
#define EQF_LOOK0 4
#define EQF_LOOK 4
constexpr int PT = EQF_PT;
constexpr int PCAP = 416;
constexpr int PSTR = PCAP + 8;
constexpr int NPBUF = 4;

constexpr int OFF_SC = 0;
constexpr int OFF_SS = OFF_SC + (SLOTA + SLOTB) * 8;
constexpr int OFF_X = (OFF_SS + (SLOTA + SLOTB) * 2 + 127) / 128 * 128;
constexpr int OFF_S = OFF_X + 98304;
constexpr int OFF_OUT = OFF_S + RING * TILE;
constexpr int OFF_OFFS = OFF_OUT + 2 * 8 * OROW;
constexpr int OFF_EPS = OFF_OFFS + 224 * 4;
constexpr int OFF_BAR = OFF_EPS + 128;
constexpr int OFF_MISC = OFF_BAR + 256;
constexpr int OFF_OFFV = OFF_MISC + 64;
constexpr int SMEM_BYTES = OFF_OFFV + 4 * 48;
constexpr int OFF_HIST = OFF_OUT;
constexpr int OFF_LOFF = OFF_HIST + HB * 4;
constexpr int OFF_DELTA = OFF_LOFF + HB * 4;
constexpr int OFF_HIST2 = OFF_DELTA + HB * 4;
static_assert(OFF_HIST2 + 2 * 168 * 4 <= OFF_OFFS, "hist alias");
constexpr int OFF_STAGE = OFF_OUT - CH * 16;
constexpr int OFF_RD = 0;
constexpr int OFF_RS = OFF_RD + CH * 4;
constexpr int OFF_RA = OFF_RS + CH * 4;
constexpr int OFF_RY = OFF_RA + CH * 2;
static_assert(OFF_RY + CH * 6 <= OFF_STAGE, "phase 1 alias");
static_assert(OFF_RA % 16 == 0 && OFF_RY % 16 == 0 && OFF_STAGE % 16 == 0, "align");
static_assert(NT >= 128 + NH, "phase 1 roles");
static_assert(OFF_S % 16 == 0 && OFF_OUT % 16 == 0 && OFF_BAR % 8 == 0 && OFF_EPS % 16 == 0, "align");
static_assert(SMEM_BYTES <= 232448, "smem");
static_assert((long long)NB * CH >= NE && NB * NPB >= NN, "cover");
static_assert((2 * RING + 1 + R1 + 4 + NPBUF) * 8 <= 256, "bars");
static_assert(NPBUF * PSTR <= SLOTA && PSTR % 8 == 0 && OFF_SS % 16 == 0 && OFF_OFFV % 16 == 0, "pool");
static_assert(HA % 8 == 0 && NLA * 32 <= 160 && NLB * 32 <= 160 && SLOTA + SLOTB < 65536 && NT == 2 * NTM, "halves");

__device__ uint4 g_rec[(size_t)NB * (CAPA + CAPB)];
__device__ unsigned int g_cnt[NH];
__device__ unsigned int g_pool;
__device__ uint4 g_ph[NB * PT * 3];
__device__ uint4 g_psc[NB * PT * PSTR / 2];
__device__ uint4 g_pss[NB * PT * PSTR / 8];
__device__ uint4 g_wfrag[20 * 128];
__device__ unsigned long long g_bar[3 * 16];
#define TS(i)
#define TSW(i)
#define DBG(i, cond)
#define TM(i)

__device__ __forceinline__ uint32_t smem_u32(const void* p) { return (uint32_t)__cvta_generic_to_shared(p); }

__device__ __forceinline__ uint4 ldg_cg_u4(const void* p, uint64_t pol) {
  uint4 v;
  asm volatile("ld.global.cg.L2::cache_hint.v4.u32 {%0,%1,%2,%3}, [%4], %5;"
               : "=r"(v.x), "=r"(v.y), "=r"(v.z), "=r"(v.w) : "l"(p), "l"(pol) : "memory");
  return v;
}
__device__ __forceinline__ void mbar_init(uint32_t bar, uint32_t cnt) {
  asm volatile("mbarrier.init.shared::cta.b64 [%0], %1;" ::"r"(bar), "r"(cnt) : "memory");
}
__device__ __forceinline__ void mbar_arrive(uint32_t bar) {
  asm volatile("mbarrier.arrive.shared::cta.b64 _, [%0];" ::"r"(bar) : "memory");
}
__device__ __forceinline__ void mbar_arrive_lane0(uint32_t bar, int lane) {
  asm volatile("{\n.reg .pred p;\nsetp.eq.s32 p, %1, 0;\n@p mbarrier.arrive.shared::cta.b64 _, [%0];\n}" ::"r"(bar), "r"(lane) : "memory");
}
__device__ __forceinline__ void mbar_wait(uint32_t bar, uint32_t parity) {
  uint32_t done;
  int it = 0;
  do {
    asm volatile("{\n.reg .pred p;\nmbarrier.try_wait.parity.shared::cta.b64 p, [%1], %2;\nselp.u32 %0, 1, 0, p;\n}"
                 : "=r"(done) : "r"(bar), "r"(parity) : "memory");
  } while (!done && ++it < (1 << 22));
}
__device__ __forceinline__ void bulk_load(uint32_t dst, const void* src, uint32_t bytes, uint32_t bar, uint64_t pol,
                                          uint32_t expect) {
  if (expect) asm volatile("mbarrier.arrive.expect_tx.shared::cta.b64 _, [%0], %1;" ::"r"(bar), "r"(expect) : "memory");
  asm volatile("cp.async.bulk.shared::cluster.global.mbarrier::complete_tx::bytes.L2::cache_hint [%0], [%1], %2, [%3], %4;"
               ::"r"(dst), "l"(src), "r"(bytes), "r"(bar), "l"(pol) : "memory");
}
__device__ __forceinline__ bool mbar_try(uint32_t bar, uint32_t parity) {
  uint32_t done;
  asm volatile("{\n.reg .pred p;\nmbarrier.test_wait.parity.shared::cta.b64 p, [%1], %2;\nselp.u32 %0, 1, 0, p;\n}"
               : "=r"(done) : "r"(bar), "r"(parity) : "memory");
  return done != 0;
}
__device__ __forceinline__ void fence_async_smem() { asm volatile("fence.proxy.async.shared::cta;" ::: "memory"); }
__device__ __forceinline__ uint32_t pack_bf16(float lo, float hi) {
  uint32_t r;
  asm("cvt.rn.bf16x2.f32 %0, %1, %2;" : "=r"(r) : "f"(hi), "f"(lo));
  return r;
}
__device__ __forceinline__ float bf_lo(uint32_t v) { return __uint_as_float(v << 16); }
__device__ __forceinline__ float bf_hi(uint32_t v) { return __uint_as_float(v & 0xffff0000u); }

__device__ __forceinline__ void mma16808(float* c, uint32_t a0, uint32_t a1, uint32_t b) {
  asm volatile("mma.sync.aligned.m16n8k8.row.col.f32.bf16.bf16.f32 {%0,%1,%2,%3}, {%4,%5}, {%6}, {%0,%1,%2,%3};"
               : "+f"(c[0]), "+f"(c[1]), "+f"(c[2]), "+f"(c[3]) : "r"(a0), "r"(a1), "r"(b));
}

__device__ __forceinline__ uint64_t make_desc(uint32_t addr, uint32_t lbo, uint32_t sbo) {
  return (uint64_t)((addr & 0x3FFFF) >> 4) | ((uint64_t)(lbo >> 4) << 16) | ((uint64_t)(sbo >> 4) << 32);
}
__device__ __forceinline__ void wgmma_n8(float* d, const uint32_t* a, uint64_t db, int scale_d) {
  asm volatile(
      "{\n.reg .pred p;\nsetp.ne.b32 p, %9, 0;\n"
      "wgmma.mma_async.sync.aligned.m64n8k16.f32.bf16.bf16 {%0,%1,%2,%3}, {%4,%5,%6,%7}, %8, p, 1, 1, 0;\n}"
      : "+f"(d[0]), "+f"(d[1]), "+f"(d[2]), "+f"(d[3])
      : "r"(a[0]), "r"(a[1]), "r"(a[2]), "r"(a[3]), "l"(db), "r"(scale_d));
}
__device__ __forceinline__ void wgmma_n24(float* d, const uint32_t* a, uint64_t db, int scale_d) {
  asm volatile(
      "{\n.reg .pred p;\nsetp.ne.b32 p, %17, 0;\n"
      "wgmma.mma_async.sync.aligned.m64n24k16.f32.bf16.bf16 {%0,%1,%2,%3,%4,%5,%6,%7,%8,%9,%10,%11}, {%12,%13,%14,%15}, %16, p, 1, 1, 0;\n}"
      : "+f"(d[0]), "+f"(d[1]), "+f"(d[2]), "+f"(d[3]), "+f"(d[4]), "+f"(d[5]), "+f"(d[6]), "+f"(d[7]),
        "+f"(d[8]), "+f"(d[9]), "+f"(d[10]), "+f"(d[11])
      : "r"(a[0]), "r"(a[1]), "r"(a[2]), "r"(a[3]), "l"(db), "r"(scale_d));
}
__device__ __forceinline__ void wgmma_n72(float* d, const uint32_t* a, uint64_t db, int scale_d) {
  asm volatile(
      "{\n.reg .pred p;\nsetp.ne.b32 p, %41, 0;\n"
      "wgmma.mma_async.sync.aligned.m64n72k16.f32.bf16.bf16 "
      "{%0,%1,%2,%3,%4,%5,%6,%7,%8,%9,%10,%11,%12,%13,%14,%15,%16,%17,"
      "%18,%19,%20,%21,%22,%23,%24,%25,%26,%27,%28,%29,%30,%31,%32,%33,%34,%35}, {%36,%37,%38,%39}, %40, p, 1, 1, 0;\n}"
      : "+f"(d[0]), "+f"(d[1]), "+f"(d[2]), "+f"(d[3]), "+f"(d[4]), "+f"(d[5]), "+f"(d[6]), "+f"(d[7]),
        "+f"(d[8]), "+f"(d[9]), "+f"(d[10]), "+f"(d[11]), "+f"(d[12]), "+f"(d[13]), "+f"(d[14]), "+f"(d[15]),
        "+f"(d[16]), "+f"(d[17]), "+f"(d[18]), "+f"(d[19]), "+f"(d[20]), "+f"(d[21]), "+f"(d[22]), "+f"(d[23]),
        "+f"(d[24]), "+f"(d[25]), "+f"(d[26]), "+f"(d[27]), "+f"(d[28]), "+f"(d[29]), "+f"(d[30]), "+f"(d[31]),
        "+f"(d[32]), "+f"(d[33]), "+f"(d[34]), "+f"(d[35])
      : "r"(a[0]), "r"(a[1]), "r"(a[2]), "r"(a[3]), "l"(db), "r"(scale_d));
}

struct Params {
  const __nv_bfloat16* x;
  const __nv_bfloat16* rhat;
  const __nv_bfloat16* eattr;
  const int* src;
  const int* dst;
  const __nv_bfloat16* wrad;
  const __nv_bfloat16* w0;
  const __nv_bfloat16* w1;
  const __nv_bfloat16* eps;
  __nv_bfloat16* out;
};

__device__ __noinline__ void slow_path(const Params& p, unsigned char* smem, int bin) {
  const int warp = threadIdx.x >> 5, lane = threadIdx.x & 31;
  float* S = reinterpret_cast<float*>(smem) + warp * 1024;
  float* P = reinterpret_cast<float*>(smem) + (NT / 32) * 1024 + warp * 768;
  const int n0 = bin * NPB, n1 = min(n0 + NPB, NN);
  for (int n = n0 + warp; n < n1; n += NT / 32) {
    float acc[4][8];
#pragma unroll
    for (int j = 0; j < 4; j++)
#pragma unroll
      for (int c = 0; c < 8; c++) acc[j][c] = 0.f;
    for (int e0 = 0; e0 < NE; e0 += 32) {
      const int e = e0 + lane;
      const bool m = (e < NE) && (p.dst[e] == n);
      unsigned bal = __ballot_sync(0xffffffffu, m);
      while (bal) {
        const int l = __ffs(bal) - 1;
        bal &= bal - 1;
        const int ee = e0 + l;
        const float a = __bfloat162float(p.eattr[ee]);
        const float cf[4] = {a, a * __bfloat162float(p.rhat[ee * 3]), a * __bfloat162float(p.rhat[ee * 3 + 1]),
                             a * __bfloat162float(p.rhat[ee * 3 + 2])};
        const uint4 v = *reinterpret_cast<const uint4*>(p.x + (size_t)p.src[ee] * 256 + lane * 8);
        const uint32_t w[4] = {v.x, v.y, v.z, v.w};
#pragma unroll
        for (int c = 0; c < 4; c++) {
#pragma unroll
          for (int j = 0; j < 4; j++) {
            acc[j][2 * c] += cf[j] * bf_lo(w[c]);
            acc[j][2 * c + 1] += cf[j] * bf_hi(w[c]);
          }
        }
      }
    }
#pragma unroll
    for (int j = 0; j < 4; j++)
#pragma unroll
      for (int c = 0; c < 8; c++) S[j * 256 + lane * 8 + c] = acc[j][c];
    __syncwarp();
    for (int c = lane; c < 64; c += 32) {
      float wr[5];
      for (int k = 0; k < 5; k++) wr[k] = __bfloat162float(p.wrad[k * 64 + c]);
      P[c] = wr[0] * S[c];
      P[64 + c] = wr[1] * (S[256 + 64 + c] + S[512 + 128 + c] + S[768 + 192 + c]);
      for (int i = 0; i < 3; i++) {
        P[128 + i * 192 + c] = wr[2] * S[(1 + i) * 256 + c];
        P[128 + i * 192 + 64 + c] = wr[3] * S[(1 + i) * 64 + c];
        float t = 0.f;
        for (int j = 0; j < 3; j++)
          for (int k = 0; k < 3; k++)
            t += __bfloat162float(p.eps[i * 9 + j * 3 + k]) * S[(1 + j) * 256 + (1 + k) * 64 + c];
        P[128 + i * 192 + 128 + c] = wr[4] * t;
      }
    }
    __syncwarp();
    for (int c = lane; c < 64; c += 32) {
      float a0 = 0.f, a1[3] = {0.f, 0.f, 0.f};
      for (int k = 0; k < 128; k++) a0 += P[k] * __bfloat162float(p.w0[k * 64 + c]);
      for (int k = 0; k < 192; k++) {
        const float w = __bfloat162float(p.w1[k * 64 + c]);
        for (int i = 0; i < 3; i++) a1[i] += P[128 + i * 192 + k] * w;
      }
      const float gate = 1.f / (1.f + __expf(-a0));
      p.out[(size_t)n * 256 + c] = __float2bfloat16(a0);
      for (int i = 0; i < 3; i++) p.out[(size_t)n * 256 + 64 + i * 64 + c] = __float2bfloat16(a1[i] * gate);
    }
    __syncwarp();
  }
}

#define EQF_EARLY 1

#define EQF_BW 8

struct Stage {
  uint32_t b1, b2;
  int meta;
};

__global__ void __launch_bounds__(NT, 1) eqf_kernel(const __grid_constant__ Params p) {
  extern __shared__ __align__(128) unsigned char smem[];
  const int tid = threadIdx.x, warp = tid >> 5, lane = tid & 31;
  const int bin = blockIdx.x;
  uint4* stage = reinterpret_cast<uint4*>(smem + OFF_STAGE);
  uint32_t* offs = reinterpret_cast<uint32_t*>(smem + OFF_OFFS);
  uint32_t* hist = reinterpret_cast<uint32_t*>(smem + OFF_HIST);
  uint32_t* hist2 = reinterpret_cast<uint32_t*>(smem + OFF_HIST2);
  uint32_t* loff = reinterpret_cast<uint32_t*>(smem + OFF_LOFF);
  uint32_t* delta = reinterpret_cast<uint32_t*>(smem + OFF_DELTA);
  volatile uint32_t* misc = reinterpret_cast<volatile uint32_t*>(smem + OFF_MISC);
  uint2* sc = reinterpret_cast<uint2*>(smem + OFF_SC);
  uint16_t* ss = reinterpret_cast<uint16_t*>(smem + OFF_SS);
  const uint32_t sbase = smem_u32(smem);
  const uint32_t bar_full = sbase + OFF_BAR, bar_empty = bar_full + 8 * RING;
  const uint32_t bar_in = bar_empty + 8 * RING;
  const uint32_t bar_cnt = bar_in + 8 * (1 + R1);
  const uint32_t bar_stg = bar_cnt + 8;
  const uint32_t bar_b = bar_stg + 8;
  const uint32_t bar_a1 = bar_b + 8;
  const uint32_t bar_info = bar_a1 + 8;

  TS(0);
  uint64_t pol_stream;
  asm volatile("createpolicy.fractional.L2::evict_first.b64 %0, 1.0;" : "=l"(pol_stream));

  const int e0 = bin * CH;
  const int nE = min(CH, NE - e0);
  unsigned long long bar_target = 0;
  auto load_payload = [&](const int r) {
    const int nr = min(NT * 4, nE - r * NT * 4);
    if (nr > 0) {
      const int o = r * NT * 4;
      bulk_load(sbase + OFF_RS + o * 4, p.src + e0 + o, nr * 4, bar_in + 8 * (1 + r), pol_stream, nr * 12);
      bulk_load(sbase + OFF_RA + o * 2, p.eattr + e0 + o, nr * 2, bar_in + 8 * (1 + r), pol_stream, 0);
      bulk_load(sbase + OFF_RY + o * 6, p.rhat + (size_t)(e0 + o) * 3, nr * 6, bar_in + 8 * (1 + r), pol_stream, 0);
    }
  };
  if (tid == 0) {
    for (int s = 0; s <= R1; s++) mbar_init(bar_in + 8 * s, 1);
    asm volatile("fence.mbarrier_init.release.cluster;" ::: "memory");
    fence_async_smem();
    bulk_load(sbase + OFF_RD, p.dst + e0, nE * 4, bar_in, pol_stream, nE * 4);
#pragma unroll
    for (int r = 0; r < EQF_EARLY; r++) load_payload(r);
    for (int s = 0; s < RING; s++) {
      mbar_init(bar_full + 8 * s, 8);
      mbar_init(bar_empty + 8 * s, 4);
    }
    mbar_init(bar_cnt, 1);
    mbar_init(bar_stg, EQF_BW);
    mbar_init(bar_b, NTM / 32);
    mbar_init(bar_a1, 1);
    for (int s = 0; s < NPBUF; s++) mbar_init(bar_info + 8 * s, 1);
    asm volatile("fence.mbarrier_init.release.cluster;" ::: "memory");
    misc[2] = 0;
    misc[3] = 0;
    misc[4] = 0x7fffffffu;
    if (bin == 0) g_pool = 0;
  }
  if (tid == 0 || tid == NTM) {
    unsigned long long v0;
    asm volatile("ld.relaxed.gpu.global.u64 %0, [%1];" : "=l"(v0) : "l"(&g_bar[tid == 0 ? 0 : 16]) : "memory");
    bar_target = (v0 / NB + 1) * NB;
    if (tid == 0) misc[6] = (uint32_t)(bar_target / NB);
  }
  if (tid < HB) hist[tid] = 0;
  if (tid < 336) hist2[tid] = 0;
  const int wfw = bin * 78 + tid - (NT - 96);
  const bool wf_on = (tid >= NT - 96) && (tid - (NT - 96) < 78) && (wfw < 10240);
  unsigned short wf0 = 0, wf1 = 0, wf2 = 0, wf3 = 0;
  if (wf_on) {
    const int r = wfw & 3, et = (wfw >> 2) & 127, ks = (wfw >> 9) & 3, mat = wfw >> 11;
    const int m = (et >> 5) * 16 + ((et & 31) >> 2) + (r & 1) * 8;
    const int pk = ks * 16 + (r >> 1) * 8 + 2 * (et & 3);
    const int ch0 = 8 * (pk & 7) + (pk >> 3), ch1 = ch0 + 8;
    const unsigned short* W = reinterpret_cast<const unsigned short*>(mat < 2 ? p.w0 + mat * 4096 : p.w1 + (mat - 2) * 4096);
    const unsigned short* wr = reinterpret_cast<const unsigned short*>(p.wrad) + mat * 64;
    wf0 = __ldg(W + ch0 * 64 + m); wf1 = __ldg(wr + ch0);
    wf2 = __ldg(W + ch1 * 64 + m); wf3 = __ldg(wr + ch1);
  }
  __syncthreads();
  mbar_wait(bar_in, 0);
  if (tid == 0) {
#pragma unroll
    for (int r = EQF_EARLY; r < R1; r++) load_payload(r);
  }
  uint32_t key[R1 * 4];
#pragma unroll
  for (int r = 0; r < R1; r++) {
    const int q = min((tid + r * NT) * 4, nE - 4);
    const int4 dv = *reinterpret_cast<const int4*>(smem + OFF_RD + q * 4);
    const bool act = (tid + r * NT) * 4 < nE;
    const int d4[4] = {dv.x, dv.y, dv.z, dv.w};
#pragma unroll
    for (int i = 0; i < 4; i++) {
      const uint32_t b0 = (uint32_t)d4[i] / NPB;
      const uint32_t dl = (uint32_t)d4[i] - b0 * NPB;
      const uint32_t b = act ? (dl >= (uint32_t)HA ? b0 + NB : b0) : (uint32_t)NH;
      const uint32_t rank = atomicAdd(&hist[b], 1u);
      key[r * 4 + i] = (b << 21) | (dl << 13) | rank;
    }
  }
  __syncthreads();
  TS(1);
  uint32_t my_cnt = 0, my_g = 0;
  if (warp == 0) {
    uint32_t c[9], s = 0;
#pragma unroll
    for (int j = 0; j < 9; j++) {
      const int b = lane * 9 + j;
      c[j] = (b < NH) ? hist[b] : 0;
      s += c[j];
    }
    uint32_t incl = s;
#pragma unroll
    for (int o = 1; o < 32; o <<= 1) {
      const uint32_t t = __shfl_up_sync(0xffffffffu, incl, o);
      if (lane >= o) incl += t;
    }
    const uint32_t gap = CH - __shfl_sync(0xffffffffu, incl, 31);
    uint32_t ex = incl - s;
#pragma unroll
    for (int j = 0; j < 9; j++) {
      const int b = lane * 9 + j;
      if (b == NB) misc[7] = ex;
      if (b <= NH) loff[b] = ex + (b >= NB ? gap : 0u);
      ex += c[j];
    }
  } else if (tid >= 128 && tid - 128 < NH) {
    my_cnt = hist[tid - 128];
    my_g = atomicAdd(&g_cnt[tid - 128], my_cnt);
  }
  __syncthreads();
#pragma unroll
  for (int r = 0; r < R1; r++) {
    const int q = min((tid + r * NT) * 4, nE - 4);
    if (r * NT * 4 < nE) mbar_wait(bar_in + 8 * (1 + r), 0);
    const uint4 sv = *reinterpret_cast<const uint4*>(smem + OFF_RS + q * 4);
    const uint2 av = *reinterpret_cast<const uint2*>(smem + OFF_RA + q * 2);
    const uint2 y0 = *reinterpret_cast<const uint2*>(smem + OFF_RY + q * 6);
    const uint2 y1 = *reinterpret_cast<const uint2*>(smem + OFF_RY + q * 6 + 8);
    const uint2 y2 = *reinterpret_cast<const uint2*>(smem + OFF_RY + q * 6 + 16);
    const uint32_t s4[4] = {sv.x, sv.y, sv.z, sv.w};
    const float a4[4] = {bf_lo(av.x), bf_hi(av.x), bf_lo(av.y), bf_hi(av.y)};
    const uint32_t w[6] = {y0.x, y0.y, y1.x, y1.y, y2.x, y2.y};
#pragma unroll
    for (int i = 0; i < 4; i++) {
      const uint32_t k = key[r * 4 + i];
      float y[3];
#pragma unroll
      for (int j = 0; j < 3; j++) {
        const int h = i * 3 + j;
        y[j] = (h & 1) ? bf_hi(w[h >> 1]) : bf_lo(w[h >> 1]);
      }
      uint4 rec;
      rec.x = pack_bf16(a4[i], a4[i] * y[0]);
      rec.y = pack_bf16(a4[i] * y[1], a4[i] * y[2]);
      rec.z = s4[i] | (((k >> 13) & 0xffu) << 16);
      rec.w = k >> 21;
      if (rec.w < (uint32_t)NH) stage[loff[rec.w] + (k & 0x1fffu)] = rec;
    }
  }
  if (tid >= 128 && tid - 128 < NH) {
    const int b = tid - 128;
    const uint32_t cap = (b < NB) ? CAPA : CAPB;
    const uint32_t base = (b < NB) ? b * CAPA : NB * CAPA + (b - NB) * CAPB;
    delta[b] = (my_g + my_cnt <= cap) ? base + my_g - loff[b] : 0xffffffffu;
  }
  if (wf_on) {
    const float v0 = __uint_as_float((uint32_t)wf0 << 16) * __uint_as_float((uint32_t)wf1 << 16);
    const float v1 = __uint_as_float((uint32_t)wf2 << 16) * __uint_as_float((uint32_t)wf3 << 16);
    reinterpret_cast<uint32_t*>(g_wfrag)[wfw] = pack_bf16(v0, v1);
  }
  __syncthreads();
  TS(2);
  const int nA = (int)misc[7], b0 = (int)loff[NB];
  auto write_out = [&](const int i) {
    const uint4 rec = stage[i];
    const uint32_t d = delta[rec.w];
    if (d != 0xffffffffu) {
      asm volatile("st.global.v4.u32 [%0], {%1,%2,%3,%4};"
                   ::"l"(g_rec + (d + i)), "r"(rec.x), "r"(rec.y), "r"(rec.z), "r"(rec.w) : "memory");
    }
  };
  for (int i = tid; i < nA; i += NT) write_out(i);
  __syncthreads();
  TS(3);

  const int n0 = bin * NPB;
  const int nn = min(NPB, NN - n0);
  const int nn8 = (nn + 7) & ~7;
  uint32_t cntA = 0, cntB = 0;

  auto sort_half = [&](auto Rc, auto NLc, const int bid, const int t0, const int half, const uint32_t cnt,
                       const uint32_t* rx, const uint32_t* ry, const uint32_t* rz) {
    constexpr int R = decltype(Rc)::value, NL = decltype(NLc)::value;
    uint32_t* h2 = hist2 + half * 168;
    const uint32_t nb0 = half * HA, sbase0 = half * SLOTA;
    uint32_t rk[R];
#pragma unroll
    for (int r = 0; r < R; r++) {
      const uint32_t i = t0 + r * NTM;
      const uint32_t dl = (i < cnt) ? (rz[r] >> 16) - nb0 : 164u;
      rk[r] = atomicAdd(&h2[dl], 1u);
    }
    asm volatile("bar.sync %0, %1;" ::"r"(bid), "n"(NTM) : "memory");
    if (t0 < 32) {
      uint32_t c[NL], s = 0;
#pragma unroll
      for (int j = 0; j < NL; j++) {
        c[j] = h2[t0 * NL + j];
        s += c[j];
      }
      uint32_t incl = s;
#pragma unroll
      for (int o = 1; o < 32; o <<= 1) {
        const uint32_t t = __shfl_up_sync(0xffffffffu, incl, o);
        if (t0 >= o) incl += t;
      }
      uint32_t ex = incl - s + sbase0;
#pragma unroll
      for (int j = 0; j < NL; j++) {
        if (half == 1 || t0 * NL + j < HA) offs[nb0 + t0 * NL + j] = ex | ((ex + c[j]) << 16);
        ex += c[j];
      }
    }
    if (t0 >= 32 && t0 < 40) {
      sc[sbase0 + cnt + (t0 - 32)] = make_uint2(0u, 0u);
      ss[sbase0 + cnt + (t0 - 32)] = 0;
    }
    asm volatile("bar.sync %0, %1;" ::"r"(bid), "n"(NTM) : "memory");
#pragma unroll
    for (int r = 0; r < R; r++) {
      const uint32_t i = t0 + r * NTM;
      if (i < cnt) {
        const uint32_t pp = (offs[rz[r] >> 16] & 0xffffu) + rk[r];
        sc[pp] = make_uint2(rx[r], ry[r]);
        ss[pp] = (uint16_t)rz[r];
      }
    }
  };

  if (tid == 0) {
    asm volatile("red.release.gpu.global.add.u64 [%0], 1;" ::"l"(&g_bar[0]) : "memory");
    mbar_arrive(bar_a1);
    TS(6);
  }
  if (tid >= NT - EQF_BW * 32) {
    mbar_wait(bar_a1, 0);
    for (int i = b0 + tid - (NT - EQF_BW * 32); i < CH; i += EQF_BW * 32) write_out(i);
    __syncwarp();
    mbar_arrive_lane0(bar_stg, lane);
  }

  if (tid < NTM) {
    if (tid == 0) {
      unsigned long long v;
      int it = 0;
      do {
        asm volatile("ld.acquire.gpu.global.u64 %0, [%1];" : "=l"(v) : "l"(&g_bar[0]) : "memory");
      } while (v < bar_target && ++it < (1 << 22));
    }
    asm volatile("bar.sync 2, %0;" ::"n"(NTM) : "memory");
    TS(4);
    uint32_t rx[R2A], ry[R2A], rz[R2A];
#pragma unroll
    for (int r = 0; r < R2A; r++) {
      const uint32_t i = min(tid + r * NTM, CAPA - 1);
      const uint4 v = ldg_cg_u4(g_rec + (size_t)bin * CAPA + i, pol_stream);
      rx[r] = v.x; ry[r] = v.y; rz[r] = v.z;
    }
    if (tid == 0) {
      uint32_t ca, cb;
      asm volatile("ld.relaxed.gpu.global.u32 %0, [%1];" : "=r"(ca) : "l"(&g_cnt[bin]) : "memory");
      asm volatile("ld.relaxed.gpu.global.u32 %0, [%1];" : "=r"(cb) : "l"(&g_cnt[NB + bin]) : "memory");
      misc[0] = ca;
      misc[1] = cb;
      g_cnt[bin] = 0;
      g_cnt[NB + bin] = 0;
      mbar_arrive(bar_cnt);
    }
    asm volatile("bar.sync 2, %0;" ::"n"(NTM) : "memory");
    cntA = misc[0];
    cntB = misc[1];
    if (cntA <= (uint32_t)CAPA && cntB <= (uint32_t)CAPB) {
      sort_half(std::integral_constant<int, R2A>{}, std::integral_constant<int, NLA>{}, 2, tid, 0, cntA, rx, ry, rz);
      asm volatile("bar.sync 2, %0;" ::"n"(NTM) : "memory");
    }
    TS(5);
  } else {
    const int tb = tid - NTM;
    asm volatile("bar.sync 3, %0;" ::"n"(NTM) : "memory");
    if (tb == 0) {
      TSW(9);
      asm volatile("red.release.gpu.global.add.u64 [%0], 1;" ::"l"(&g_bar[16]) : "memory");
      unsigned long long v;
      int it = 0;
      do {
        asm volatile("ld.acquire.gpu.global.u64 %0, [%1];" : "=l"(v) : "l"(&g_bar[16]) : "memory");
      } while (v < bar_target && ++it < (1 << 22));
    }
    asm volatile("bar.sync 3, %0;" ::"n"(NTM) : "memory");
    if (tb == 0) TSW(11);
    uint32_t rx[R2B], ry[R2B], rz[R2B];
#pragma unroll
    for (int r = 0; r < R2B; r++) {
      const uint32_t i = min(tb + r * NTM, CAPB - 1);
      const uint4 v = ldg_cg_u4(g_rec + (size_t)NB * CAPA + (size_t)bin * CAPB + i, pol_stream);
      rx[r] = v.x; ry[r] = v.y; rz[r] = v.z;
    }
    mbar_wait(bar_cnt, 0);
    cntA = misc[0];
    cntB = misc[1];
    if (cntA <= (uint32_t)CAPA && cntB <= (uint32_t)CAPB) {
      sort_half(std::integral_constant<int, R2B>{}, std::integral_constant<int, NLB>{}, 3, tb, 1, cntB, rx, ry, rz);
      if (tb == 0) {
        int own = nn8;
        if ((nn8 >> 3) - PT >= HA / 8 + 2) {
          bool fits = true;
          for (int j = 0; j < PT; j++) {
            const int nb = nn8 - 8 * (PT - j);
            fits = fits && ((offs[nb + 7] >> 16) - (offs[nb] & 0xffffu) <= (uint32_t)PCAP);
          }
          if (fits) own = nn8 - 8 * PT;
        }
        misc[5] = (uint32_t)own;
      }
      __syncwarp();
      mbar_arrive_lane0(bar_b, lane);
    }
    if (tb == 0) TSW(13);
  }
  if (cntA > (uint32_t)CAPA || cntB > (uint32_t)CAPB) {
    mbar_wait(bar_stg, 0);
    if (tid == 0) {
      for (int j = 0; j < PT * 3; j++) g_ph[bin * PT * 3 + j] = make_uint4(0u, 0u, 0u, 0u);
      asm volatile("red.release.gpu.global.add.u64 [%0], 1;" ::"l"(&g_bar[32]) : "memory");
    }
    slow_path(p, smem, bin);
    return;
  }

  if (warp < GW) {
    asm volatile("setmaxnreg.dec.sync.aligned.u32 %0;" ::"n"(EQF_REG_G));
    const int g = lane >> 2, t = lane & 3, q = lane >> 3;
    const char* xq = reinterpret_cast<const char*>(p.x) + (lane & 7) * 16;
    const uint32_t xs = sbase + OFF_X + warp * NST * 4096;
    const uint32_t cd0 = xs + q * 512 + (((lane & 7) ^ q) * 16);
    const uint32_t cd1 = xs + (4 + q) * 512 + (((lane & 7) ^ (4 + q)) * 16);
    const uint32_t la0 = xs + (lane & 7) * 512 + ((q ^ (lane & 7)) * 16);
    const uint32_t la1 = xs + (lane & 7) * 512 + (((4 + q) ^ (lane & 7)) * 16);
    const uint32_t sc_s = sbase + OFF_SC + t * 16 + (g & 3) * 2;
    const uint32_t ss_s = sbase + OFF_SS + q * 2;
    const uint32_t mask1 = (g < 4) ? 0xffffffffu : 0u;
    uint32_t st[4];
#pragma unroll
    for (int c = 0; c < 4; c++) {
      const int blk = 2 * (c >> 1) + (t >> 1), jj = 2 * (t & 1) + (c & 1);
      const int a = (blk == 0) ? (jj == 0 ? 15 : 11 + jj) : (jj == 0 ? 8 + blk : 3 * (jj - 1) + (blk - 1));
      st[c] = sbase + OFF_S + a * ATOM + g * LBO_S;
    }
    float acc[8][4];
#pragma unroll
    for (int i = 0; i < 8; i++) acc[i][0] = acc[i][1] = acc[i][2] = acc[i][3] = 0.f;

    const volatile uint32_t* offv = reinterpret_cast<const volatile uint32_t*>(smem + OFF_OFFV);
    if (warp == GW - 1) {
      mbar_wait(bar_b, 0);
      const int own = (int)misc[5];
      {
        uint2* gsc = reinterpret_cast<uint2*>(g_psc);
        unsigned short* gss = reinterpret_cast<unsigned short*>(g_pss);
        uint32_t* gph = reinterpret_cast<uint32_t*>(g_ph);
#pragma unroll 1
        for (int j = 0; j < PT; j++) {
          const int e = bin * PT + j;
          uint32_t h = 0;
          if (own < nn8) {
            const int nb = own + 8 * j;
            const uint32_t beg = offs[nb] & 0xffffu, cnt = (offs[nb + 7] >> 16) - beg;
            for (uint32_t i = lane; i < cnt + 8; i += 32) {
              gsc[e * PSTR + i] = (i < cnt) ? sc[beg + i] : make_uint2(0u, 0u);
              gss[e * PSTR + i] = (i < cnt) ? ss[beg + i] : (unsigned short)0;
            }
            if (lane < 8) h = offs[nb + lane] - beg * 0x10001u;
            else if (lane == 8) h = (uint32_t)(n0 + nb);
            else if (lane == 9) h = (uint32_t)max(0, min(8, nn - nb));
          } else if (lane < 8) {
            gsc[e * PSTR + lane] = make_uint2(0u, 0u);
            gss[e * PSTR + lane] = 0;
          }
          if (lane < 12) gph[e * 12 + lane] = h;
        }
      }
      __syncwarp();
      __threadfence();
      __syncwarp();
      if (lane == 0) {
        asm volatile("red.release.gpu.global.add.u64 [%0], 1;" ::"l"(&g_bar[32]) : "memory");
        const unsigned long long pub_target = (unsigned long long)misc[6] * NB;
        {
          int it = 0;
          while ((int)misc[3] < HA / 8 && ++it < (1 << 22)) __nanosleep(200);
          DBG(1, it >= (1 << 22));
          unsigned long long v;
          it = 0;
          do {
            asm volatile("ld.acquire.gpu.global.u64 %0, [%1];" : "=l"(v) : "l"(&g_bar[32]) : "memory");
          } while (v < pub_target && ++it < (1 << 20));
          DBG(2, it >= (1 << 20));
          asm volatile("fence.proxy.async;" ::: "memory");
          it = 0;
          while ((int)misc[2] < own - EQF_LOOK - EQF_LOOK0 && ++it < (1 << 22)) __nanosleep(32);
        }
        uint32_t k = atomicAdd(&g_pool, 1u);
        for (int qq = 0;; qq++) {
          int it = 0;
          while ((int)misc[2] < own + 8 * qq - EQF_LOOK && ++it < (1 << 22)) __nanosleep(32);
          DBG(0, it >= (1 << 22));
          if (qq >= NPBUF) {
            const int need = (own >> 3) + qq - NPBUF + 1;
            it = 0;
            while ((int)misc[3] < need && ++it < (1 << 22)) __nanosleep(32);
            DBG(1, it >= (1 << 22));
            fence_async_smem();
          }
          TM(qq * 4 + 0);
          const int j = qq % NPBUF;
          if (k >= (uint32_t)(NB * PT)) {
            misc[4] = (uint32_t)qq;
            mbar_arrive(bar_info + 8 * j);
            break;
          }
          const uint32_t e = (k % NB) * PT + k / NB;
          bulk_load(sbase + OFF_OFFV + j * 48, &g_ph[e * 3], 48, bar_info + 8 * j, pol_stream, 48 + PSTR * 10);
          bulk_load(sbase + OFF_SS + j * PSTR * 2, &g_pss[e * (PSTR / 8)], PSTR * 2, bar_info + 8 * j, pol_stream, 0);
          bulk_load(sbase + OFF_SC + j * PSTR * 8, &g_psc[e * (PSTR / 2)], PSTR * 8, bar_info + 8 * j, pol_stream, 0);
          TM(qq * 4 + 1);
          k = atomicAdd(&g_pool, 1u);
          TM(qq * 4 + 2);
        }
      }
      return;
    }

    if (warp >= GA) return;
    if (OFF_STAGE + b0 * 16 < OFF_X + (warp + 1) * NST * 4096) mbar_wait(bar_stg, 0);
    bool s_free = false;
    int node, pos, end, pend;
    int own = HA;
    bool b_ready = false;
    auto resolve = [&]() {
      const int n = pend;
      uint32_t be;
      if (n < own) {
        be = offs[n];
      } else {
        const int qq = (n - own) >> 3, j = qq % NPBUF;
        const bool ready = __all_sync(0xffffffffu, mbar_try(bar_info + 8 * j, (qq / NPBUF) & 1));
        const int stop = __shfl_sync(0xffffffffu, (int)misc[4], 0);
        if (stop < qq || (ready && stop == qq)) {
          node = -1;
          return;
        }
        if (!ready) { node = -2; return; }
        be = offv[j * 12 + (n & 7)] + (uint32_t)(j * PSTR) * 0x10001u;
      }
      node = n;
      pos = (int)(be & 0xffffu);
      end = (int)(be >> 16);
    };
    auto next_node = [&]() {
      int n = 0;
      if (lane == 0) n = (int)atomicAdd(const_cast<uint32_t*>(&misc[2]), 1u);
      n = __shfl_sync(0xffffffffu, n, 0);
      if (n >= HA && !b_ready) {
        mbar_wait(bar_b, 0);
        own = (int)misc[5];
        b_ready = true;
      }
      pend = n;
      resolve();
    };
    auto issue = [&](Stage& B, const int i) {
      if (node == -2) resolve();
      if (node < 0) {
        B.meta = node;
        asm volatile("cp.async.commit_group;" ::: "memory");
        return;
      }
      const int cnt = end - pos;
      const bool last = (cnt <= 8);
      B.meta = node | (last ? 0x10000 : 0);
      uint32_t s0, s1, c0, c1;
      asm volatile("ld.shared.u16 %0, [%1];" : "=r"(s0) : "r"(ss_s + pos * 2));
      asm volatile("ld.shared.u16 %0, [%1+8];" : "=r"(s1) : "r"(ss_s + pos * 2));
      asm volatile("ld.shared.u16 %0, [%1];" : "=r"(c0) : "r"(sc_s + pos * 8));
      asm volatile("ld.shared.u16 %0, [%1+8];" : "=r"(c1) : "r"(sc_s + pos * 8));
      const int z0 = (q < cnt) ? 16 : 0, z1 = (4 + q < cnt) ? 16 : 0;
      const char* p0 = xq + (size_t)s0 * 512;
      const char* p1 = xq + (size_t)s1 * 512;
#pragma unroll
      for (int k = 0; k < 4; k++) {
        asm volatile("cp.async.cg.shared.global [%0], [%1], 16, %2;" ::"r"(cd0 + i * 4096 + k * 128), "l"(p0 + k * 128), "r"(z0) : "memory");
        asm volatile("cp.async.cg.shared.global [%0], [%1], 16, %2;" ::"r"(cd1 + i * 4096 + k * 128), "l"(p1 + k * 128), "r"(z1) : "memory");
      }
      asm volatile("cp.async.commit_group;" ::: "memory");
      const uint32_t m = __funnelshift_lc(0xffffffffu, 0u, (uint32_t)max(16 * min(cnt, 8) - 32 * t, 0));
      const uint32_t b = (c0 | (c1 << 16)) & m;
      B.b1 = b & mask1;
      B.b2 = b & ~mask1;
      pos += 8;
      if (last) next_node();
    };
    auto consume = [&](Stage& B, const int i) {
      asm volatile("cp.async.wait_group %0;" ::"n"(NST - 1) : "memory");
      if (B.meta < 0) return;
      __syncwarp();
#pragma unroll
      for (int j = 0; j < 8; j++) {
        uint32_t r0, r1, r2, r3;
        asm volatile("ldmatrix.sync.aligned.m8n8.x4.trans.shared.b16 {%0,%1,%2,%3}, [%4];"
                     : "=r"(r0), "=r"(r1), "=r"(r2), "=r"(r3)
                     : "r"(((j & 1) ? la1 : la0) + i * 4096 + (j >> 1) * 128) : "memory");
        const int blk = j >> 1;
        const uint32_t b = (blk & 1) ? B.b2 : B.b1;
        mma16808(acc[(blk >> 1) * 4 + (j & 1) * 2 + 0], r0, r1, b);
        mma16808(acc[(blk >> 1) * 4 + (j & 1) * 2 + 1], r2, r3, b);
      }
      if (B.meta & 0x10000) {
        const int n = B.meta & 0xffff;
        const int tl = n >> 3;
        const int slot = tl % RING;
        if (!s_free) {
          mbar_wait(bar_stg, 0);
          s_free = true;
        }
        mbar_wait(bar_empty + 8 * slot, ((tl / RING) & 1) ^ 1);
        const uint32_t o = slot * TILE + (n & 7) * 16;
#pragma unroll
        for (int c = 0; c < 4; c++) {
          uint32_t w[4];
#pragma unroll
          for (int u = 0; u < 4; u++) {
            const float* a = acc[(c >> 1) * 4 + u];
            w[u] = pack_bf16(a[c & 1], a[2 + (c & 1)]);
          }
          asm volatile("st.shared.v4.u32 [%0], {%1,%2,%3,%4};" ::"r"(st[c] + o), "r"(w[0]), "r"(w[1]), "r"(w[2]), "r"(w[3]) : "memory");
        }
#pragma unroll
        for (int u = 0; u < 8; u++) acc[u][0] = acc[u][1] = acc[u][2] = acc[u][3] = 0.f;
        __syncwarp();
        mbar_arrive_lane0(bar_full + 8 * slot, lane);
      }
      __syncwarp();
    };

    Stage B[NST];
    next_node();
#pragma unroll
    for (int i = 0; i < NST; i++) issue(B[i], i);
    bool run = true;
    int guard = 0;
    while (run && ++guard < (1 << 24)) {
#pragma unroll
      for (int i = 0; i < NST; i++) {
        if (B[i].meta == -1) { run = false; break; }
        consume(B[i], i);
        issue(B[i], i);
      }
    }
    TSW(7);
  } else {
    asm volatile("setmaxnreg.inc.sync.aligned.u32 %0;" ::"n"(EQF_REG_E));
    const int et = tid - GW * 32, ew = et >> 5;
    uint32_t wa[5][4][4];
#pragma unroll
    for (int mat = 0; mat < 5; mat++) {
#pragma unroll
      for (int ks = 0; ks < 4; ks++) {
        const uint4 v = __ldcg(&g_wfrag[(mat * 4 + ks) * 128 + et]);
        wa[mat][ks][0] = v.x; wa[mat][ks][1] = v.y; wa[mat][ks][2] = v.z; wa[mat][ks][3] = v.w;
      }
    }
    float* eps = reinterpret_cast<float*>(smem + OFF_EPS);
    if (et < 27) eps[et] = __bfloat162float(p.eps[et]);
    asm volatile("bar.sync 1, 128;" ::: "memory");

    mbar_wait(bar_b, 0);
    const int own = (int)misc[5];
    const int town = own >> 3;
    const volatile uint32_t* offv = reinterpret_cast<const volatile uint32_t*>(smem + OFF_OFFV);
    for (int tl = 0;; tl++) {
      const int slot = tl % RING;
      int row0 = n0 + tl * 8, nvalid = nn - tl * 8;
      if (tl >= town) {
        const int qq = tl - town, j = qq % NPBUF;
        bool ready = false;
        int stop = 0x7fffffff;
        for (int it = 0; it < (1 << 22); it++) {
          ready = __all_sync(0xffffffffu, mbar_try(bar_info + 8 * j, (qq / NPBUF) & 1));
          stop = __shfl_sync(0xffffffffu, (int)misc[4], 0);
          if (ready || stop < qq) break;
        }
        if (stop <= qq || !ready) break;
        row0 = (int)offv[j * 12 + 8];
        nvalid = (int)offv[j * 12 + 9];
      }
      mbar_wait(bar_full + 8 * slot, (tl / RING) & 1);
      fence_async_smem();
      const uint32_t tb = sbase + OFF_S + slot * TILE;
      float d0[4], d1[12], q[36];
      asm volatile("wgmma.fence.sync.aligned;" ::: "memory");
#pragma unroll
      for (int ks = 0; ks < 4; ks++)
        wgmma_n72(q, wa[4][ks], make_desc(tb + ks * 2 * LBO_S, LBO_S, ATOM), ks);
#pragma unroll
      for (int ks = 0; ks < 4; ks++)
        wgmma_n8(d0, wa[0][ks], make_desc(tb + 15 * ATOM + ks * 2 * LBO_S, LBO_S, ATOM), ks);
#pragma unroll
      for (int j = 0; j < 3; j++)
#pragma unroll
        for (int ks = 0; ks < 4; ks++)
          wgmma_n8(d0, wa[1][ks], make_desc(tb + 4 * j * ATOM + ks * 2 * LBO_S, LBO_S, ATOM), 1);
#pragma unroll
      for (int ks = 0; ks < 4; ks++)
        wgmma_n24(d1, wa[2][ks], make_desc(tb + 12 * ATOM + ks * 2 * LBO_S, LBO_S, ATOM), ks);
#pragma unroll
      for (int ks = 0; ks < 4; ks++)
        wgmma_n24(d1, wa[3][ks], make_desc(tb + 9 * ATOM + ks * 2 * LBO_S, LBO_S, ATOM), 1);
      asm volatile("wgmma.commit_group.sync.aligned;" ::: "memory");
      asm volatile("wgmma.wait_group.sync.aligned 0;" ::: "memory");
      mbar_arrive_lane0(bar_empty + 8 * slot, lane);

      float gate[4];
#pragma unroll
      for (int xx = 0; xx < 4; xx++) gate[xx] = __fdividef(1.f, 1.f + __expf(-d0[xx]));
      uint32_t R[4][2];
      R[0][0] = pack_bf16(d0[0], d0[1]);
      R[0][1] = pack_bf16(d0[2], d0[3]);
#pragma unroll
      for (int i = 0; i < 3; i++) {
        float o[4] = {d1[4 * i], d1[4 * i + 1], d1[4 * i + 2], d1[4 * i + 3]};
#pragma unroll
        for (int m = 0; m < 9; m++) {
          const float e = eps[i * 9 + m];
#pragma unroll
          for (int xx = 0; xx < 4; xx++) o[xx] = fmaf(e, q[4 * m + xx], o[xx]);
        }
        R[1 + i][0] = pack_bf16(o[0] * gate[0], o[1] * gate[1]);
        R[1 + i][1] = pack_bf16(o[2] * gate[2], o[3] * gate[3]);
      }
      const uint32_t ob = sbase + OFF_OUT + (tl & 1) * 8 * OROW;
      {
        const int mi = lane >> 3, j = lane & 7;
        const uint32_t a = ob + j * OROW + ((mi >> 1) * 64 + ew * 16 + (mi & 1) * 8) * 2;
        asm volatile("stmatrix.sync.aligned.m8n8.x4.trans.shared.b16 [%0], {%1,%2,%3,%4};"
                     ::"r"(a), "r"(R[0][0]), "r"(R[0][1]), "r"(R[1][0]), "r"(R[1][1]) : "memory");
        asm volatile("stmatrix.sync.aligned.m8n8.x4.trans.shared.b16 [%0], {%1,%2,%3,%4};"
                     ::"r"(a + 256), "r"(R[2][0]), "r"(R[2][1]), "r"(R[3][0]), "r"(R[3][1]) : "memory");
      }
      asm volatile("bar.sync 1, 128;" ::: "memory");
      if (et == 0) misc[3] = (uint32_t)(tl + 1);
#pragma unroll
      for (int h = 0; h < 2; h++) {
        const int c = et + 128 * h, row = c >> 5, c16 = c & 31;
        if (row < nvalid) {
          const uint4 v = *reinterpret_cast<const uint4*>(smem + OFF_OUT + (tl & 1) * 8 * OROW + row * OROW + c16 * 16);
          asm volatile("st.global.L2::cache_hint.v4.u32 [%0], {%1,%2,%3,%4}, %5;"
                       ::"l"(reinterpret_cast<char*>(p.out) + (size_t)(row0 + row) * 512 + c16 * 16),
                         "r"(v.x), "r"(v.y), "r"(v.z), "r"(v.w), "l"(pol_stream) : "memory");
        }
      }
    }
    if (ew == 0) TSW(8);
  }
}

}

extern "C" void kernel_launch(void* const* d_in, const int* in_sizes, int n_in, void* d_out, int out_size) {
  using namespace eqf;
  if (n_in < 9 || in_sizes[0] != NN * 256 || in_sizes[3] != NE || out_size != NN * 256) {
    fprintf(stderr, "kernel_launch: unexpected problem size\n");
    return;
  }
  static bool init = false;
  if (!init) {
    cudaFuncSetAttribute(eqf_kernel, cudaFuncAttributeMaxDynamicSharedMemorySize, SMEM_BYTES);
    init = true;
  }
  Params p;
  p.x = (const __nv_bfloat16*)d_in[0];
  p.rhat = (const __nv_bfloat16*)d_in[1];
  p.eattr = (const __nv_bfloat16*)d_in[2];
  p.src = (const int*)d_in[3];
  p.dst = (const int*)d_in[4];
  p.wrad = (const __nv_bfloat16*)d_in[5];
  p.w0 = (const __nv_bfloat16*)d_in[6];
  p.w1 = (const __nv_bfloat16*)d_in[7];
  p.eps = (const __nv_bfloat16*)d_in[8];
  p.out = (__nv_bfloat16*)d_out;
  eqf_kernel<<<NB, NT, SMEM_BYTES>>>(p);
}
```

```cpp
#include <cuda_runtime.h>
#include <cuda_bf16.h>
#include <stdint.h>
#include <stdio.h>
#include <type_traits>

namespace eqf {

constexpr int NN = 25000;
constexpr int NE = 800000;
constexpr int NB = 132;
constexpr int NPB = 190;
constexpr int CH = 6064;
constexpr int HA = 56;
constexpr int NH = 2 * NB;
constexpr int CAPA = 2016;
constexpr int CAPB = 4632;
constexpr int SLOTA = CAPA + 8, SLOTB = CAPB + 8;
constexpr int NLA = (HA + 31) / 32, NLB = (192 - HA + 31) / 32;
constexpr int GW = 12;
constexpr int GA = GW - 1;
constexpr int NST = 2;
constexpr int NT = (GW + 4) * 32;
constexpr int REG_G = 112, REG_E = 176;
constexpr int RING = 3;
constexpr int LBO_S = 144;
constexpr int ATOM = 1184;
constexpr int TILE = 16 * ATOM;
constexpr int OROW = 528;
constexpr int R1 = (CH / 4 + NT - 1) / NT;
constexpr int NTM = 256;
constexpr int R2A = (CAPA + NTM - 1) / NTM;
constexpr int R2B = (CAPB + NTM - 1) / NTM;
constexpr int HB = 272;
constexpr int PT = 3;
constexpr int LOOK = 4;
constexpr int PCAP = 416;
constexpr int PSTR = PCAP + 8;
constexpr int NPBUF = 4;
static_assert(GA * NST * 4096 <= 98304, "x ring");

constexpr int OFF_SC = 0;
constexpr int OFF_SS = OFF_SC + (SLOTA + SLOTB) * 8;
constexpr int OFF_X = (OFF_SS + (SLOTA + SLOTB) * 2 + 127) / 128 * 128;
constexpr int OFF_S = OFF_X + 98304;
constexpr int OFF_OUT = OFF_S + RING * TILE;
constexpr int OFF_OFFS = OFF_OUT + 2 * 8 * OROW;
constexpr int OFF_EPS = OFF_OFFS + 224 * 4;
constexpr int OFF_BAR = OFF_EPS + 128;
constexpr int OFF_MISC = OFF_BAR + 256;
constexpr int OFF_OFFV = OFF_MISC + 64;
constexpr int SMEM_BYTES = OFF_OFFV + 4 * 48;
constexpr int OFF_HIST = OFF_OUT;
constexpr int OFF_LOFF = OFF_HIST + HB * 4;
constexpr int OFF_DELTA = OFF_LOFF + HB * 4;
constexpr int OFF_HIST2 = OFF_DELTA + HB * 4;
static_assert(OFF_HIST2 + 2 * 168 * 4 <= OFF_OFFS, "hist alias");
constexpr int OFF_STAGE = OFF_OUT - CH * 16;
constexpr int OFF_RD = 0;
constexpr int OFF_RS = OFF_RD + CH * 4;
constexpr int OFF_RA = OFF_RS + CH * 4;
constexpr int OFF_RY = OFF_RA + CH * 2;
static_assert(OFF_RY + CH * 6 <= OFF_STAGE, "phase 1 alias");
static_assert(OFF_RA % 16 == 0 && OFF_RY % 16 == 0 && OFF_STAGE % 16 == 0, "align");
static_assert(NT >= 128 + NH, "phase 1 roles");
static_assert(OFF_S % 16 == 0 && OFF_OUT % 16 == 0 && OFF_BAR % 8 == 0 && OFF_EPS % 16 == 0, "align");
static_assert(SMEM_BYTES <= 232448, "smem");
static_assert((long long)NB * CH >= NE && NB * NPB >= NN, "cover");
static_assert((2 * RING + 1 + R1 + 4 + NPBUF) * 8 <= 256, "bars");
static_assert(NPBUF * PSTR <= SLOTA && PSTR % 8 == 0 && OFF_SS % 16 == 0 && OFF_OFFV % 16 == 0, "pool");
static_assert(HA % 8 == 0 && NLA * 32 <= 160 && NLB * 32 <= 160 && SLOTA + SLOTB < 65536 && NT == 2 * NTM, "halves");

__device__ uint4 g_rec[(size_t)NB * (CAPA + CAPB)];
__device__ unsigned int g_cnt[NH];
__device__ unsigned int g_pool;
__device__ uint4 g_ph[NB * PT * 3];
__device__ uint4 g_psc[NB * PT * PSTR / 2];
__device__ uint4 g_pss[NB * PT * PSTR / 8];
__device__ uint4 g_wfrag[20 * 128];
__device__ unsigned long long g_bar[3 * 16];

__device__ __forceinline__ uint32_t smem_u32(const void* p) { return (uint32_t)__cvta_generic_to_shared(p); }

__device__ __forceinline__ uint4 ldg_cg_u4(const void* p, uint64_t pol) {
  uint4 v;
  asm volatile("ld.global.cg.L2::cache_hint.v4.u32 {%0,%1,%2,%3}, [%4], %5;"
               : "=r"(v.x), "=r"(v.y), "=r"(v.z), "=r"(v.w) : "l"(p), "l"(pol) : "memory");
  return v;
}
__device__ __forceinline__ void mbar_init(uint32_t bar, uint32_t cnt) {
  asm volatile("mbarrier.init.shared::cta.b64 [%0], %1;" ::"r"(bar), "r"(cnt) : "memory");
}
__device__ __forceinline__ void mbar_arrive(uint32_t bar) {
  asm volatile("mbarrier.arrive.shared::cta.b64 _, [%0];" ::"r"(bar) : "memory");
}
__device__ __forceinline__ void mbar_arrive_lane0(uint32_t bar, int lane) {
  asm volatile("{\n.reg .pred p;\nsetp.eq.s32 p, %1, 0;\n@p mbarrier.arrive.shared::cta.b64 _, [%0];\n}" ::"r"(bar), "r"(lane) : "memory");
}
__device__ __forceinline__ void mbar_wait(uint32_t bar, uint32_t parity) {
  uint32_t done;
  int it = 0;
  do {
    asm volatile("{\n.reg .pred p;\nmbarrier.try_wait.parity.shared::cta.b64 p, [%1], %2;\nselp.u32 %0, 1, 0, p;\n}"
                 : "=r"(done) : "r"(bar), "r"(parity) : "memory");
  } while (!done && ++it < (1 << 22));
}
__device__ __forceinline__ void bulk_load(uint32_t dst, const void* src, uint32_t bytes, uint32_t bar, uint64_t pol,
                                          uint32_t expect) {
  if (expect) asm volatile("mbarrier.arrive.expect_tx.shared::cta.b64 _, [%0], %1;" ::"r"(bar), "r"(expect) : "memory");
  asm volatile("cp.async.bulk.shared::cluster.global.mbarrier::complete_tx::bytes.L2::cache_hint [%0], [%1], %2, [%3], %4;"
               ::"r"(dst), "l"(src), "r"(bytes), "r"(bar), "l"(pol) : "memory");
}
__device__ __forceinline__ bool mbar_try(uint32_t bar, uint32_t parity) {
  uint32_t done;
  asm volatile("{\n.reg .pred p;\nmbarrier.test_wait.parity.shared::cta.b64 p, [%1], %2;\nselp.u32 %0, 1, 0, p;\n}"
               : "=r"(done) : "r"(bar), "r"(parity) : "memory");
  return done != 0;
}
__device__ __forceinline__ void fence_async_smem() { asm volatile("fence.proxy.async.shared::cta;" ::: "memory"); }
__device__ __forceinline__ uint32_t pack_bf16(float lo, float hi) {
  uint32_t r;
  asm("cvt.rn.bf16x2.f32 %0, %1, %2;" : "=r"(r) : "f"(hi), "f"(lo));
  return r;
}
__device__ __forceinline__ float bf_lo(uint32_t v) { return __uint_as_float(v << 16); }
__device__ __forceinline__ float bf_hi(uint32_t v) { return __uint_as_float(v & 0xffff0000u); }

__device__ __forceinline__ void mma16808(float* c, uint32_t a0, uint32_t a1, uint32_t b) {
  asm volatile("mma.sync.aligned.m16n8k8.row.col.f32.bf16.bf16.f32 {%0,%1,%2,%3}, {%4,%5}, {%6}, {%0,%1,%2,%3};"
               : "+f"(c[0]), "+f"(c[1]), "+f"(c[2]), "+f"(c[3]) : "r"(a0), "r"(a1), "r"(b));
}

__device__ __forceinline__ uint64_t make_desc(uint32_t addr, uint32_t lbo, uint32_t sbo) {
  return (uint64_t)((addr & 0x3FFFF) >> 4) | ((uint64_t)(lbo >> 4) << 16) | ((uint64_t)(sbo >> 4) << 32);
}
__device__ __forceinline__ void wgmma_n8(float* d, const uint32_t* a, uint64_t db, int scale_d) {
  asm volatile(
      "{\n.reg .pred p;\nsetp.ne.b32 p, %9, 0;\n"
      "wgmma.mma_async.sync.aligned.m64n8k16.f32.bf16.bf16 {%0,%1,%2,%3}, {%4,%5,%6,%7}, %8, p, 1, 1, 0;\n}"
      : "+f"(d[0]), "+f"(d[1]), "+f"(d[2]), "+f"(d[3])
      : "r"(a[0]), "r"(a[1]), "r"(a[2]), "r"(a[3]), "l"(db), "r"(scale_d));
}
__device__ __forceinline__ void wgmma_n24(float* d, const uint32_t* a, uint64_t db, int scale_d) {
  asm volatile(
      "{\n.reg .pred p;\nsetp.ne.b32 p, %17, 0;\n"
      "wgmma.mma_async.sync.aligned.m64n24k16.f32.bf16.bf16 {%0,%1,%2,%3,%4,%5,%6,%7,%8,%9,%10,%11}, {%12,%13,%14,%15}, %16, p, 1, 1, 0;\n}"
      : "+f"(d[0]), "+f"(d[1]), "+f"(d[2]), "+f"(d[3]), "+f"(d[4]), "+f"(d[5]), "+f"(d[6]), "+f"(d[7]),
        "+f"(d[8]), "+f"(d[9]), "+f"(d[10]), "+f"(d[11])
      : "r"(a[0]), "r"(a[1]), "r"(a[2]), "r"(a[3]), "l"(db), "r"(scale_d));
}
__device__ __forceinline__ void wgmma_n72(float* d, const uint32_t* a, uint64_t db, int scale_d) {
  asm volatile(
      "{\n.reg .pred p;\nsetp.ne.b32 p, %41, 0;\n"
      "wgmma.mma_async.sync.aligned.m64n72k16.f32.bf16.bf16 "
      "{%0,%1,%2,%3,%4,%5,%6,%7,%8,%9,%10,%11,%12,%13,%14,%15,%16,%17,"
      "%18,%19,%20,%21,%22,%23,%24,%25,%26,%27,%28,%29,%30,%31,%32,%33,%34,%35}, {%36,%37,%38,%39}, %40, p, 1, 1, 0;\n}"
      : "+f"(d[0]), "+f"(d[1]), "+f"(d[2]), "+f"(d[3]), "+f"(d[4]), "+f"(d[5]), "+f"(d[6]), "+f"(d[7]),
        "+f"(d[8]), "+f"(d[9]), "+f"(d[10]), "+f"(d[11]), "+f"(d[12]), "+f"(d[13]), "+f"(d[14]), "+f"(d[15]),
        "+f"(d[16]), "+f"(d[17]), "+f"(d[18]), "+f"(d[19]), "+f"(d[20]), "+f"(d[21]), "+f"(d[22]), "+f"(d[23]),
        "+f"(d[24]), "+f"(d[25]), "+f"(d[26]), "+f"(d[27]), "+f"(d[28]), "+f"(d[29]), "+f"(d[30]), "+f"(d[31]),
        "+f"(d[32]), "+f"(d[33]), "+f"(d[34]), "+f"(d[35])
      : "r"(a[0]), "r"(a[1]), "r"(a[2]), "r"(a[3]), "l"(db), "r"(scale_d));
}

struct Params {
  const __nv_bfloat16* x;
  const __nv_bfloat16* rhat;
  const __nv_bfloat16* eattr;
  const int* src;
  const int* dst;
  const __nv_bfloat16* wrad;
  const __nv_bfloat16* w0;
  const __nv_bfloat16* w1;
  const __nv_bfloat16* eps;
  __nv_bfloat16* out;
};

__device__ __noinline__ void slow_path(const Params& p, unsigned char* smem, int bin) {
  const int warp = threadIdx.x >> 5, lane = threadIdx.x & 31;
  float* S = reinterpret_cast<float*>(smem) + warp * 1024;
  float* P = reinterpret_cast<float*>(smem) + (NT / 32) * 1024 + warp * 768;
  const int n0 = bin * NPB, n1 = min(n0 + NPB, NN);
  for (int n = n0 + warp; n < n1; n += NT / 32) {
    float acc[4][8];
#pragma unroll
    for (int j = 0; j < 4; j++)
#pragma unroll
      for (int c = 0; c < 8; c++) acc[j][c] = 0.f;
    for (int e0 = 0; e0 < NE; e0 += 32) {
      const int e = e0 + lane;
      const bool m = (e < NE) && (p.dst[e] == n);
      unsigned bal = __ballot_sync(0xffffffffu, m);
      while (bal) {
        const int l = __ffs(bal) - 1;
        bal &= bal - 1;
        const int ee = e0 + l;
        const float a = __bfloat162float(p.eattr[ee]);
        const float cf[4] = {a, a * __bfloat162float(p.rhat[ee * 3]), a * __bfloat162float(p.rhat[ee * 3 + 1]),
                             a * __bfloat162float(p.rhat[ee * 3 + 2])};
        const uint4 v = *reinterpret_cast<const uint4*>(p.x + (size_t)p.src[ee] * 256 + lane * 8);
        const uint32_t w[4] = {v.x, v.y, v.z, v.w};
#pragma unroll
        for (int c = 0; c < 4; c++) {
#pragma unroll
          for (int j = 0; j < 4; j++) {
            acc[j][2 * c] += cf[j] * bf_lo(w[c]);
            acc[j][2 * c + 1] += cf[j] * bf_hi(w[c]);
          }
        }
      }
    }
#pragma unroll
    for (int j = 0; j < 4; j++)
#pragma unroll
      for (int c = 0; c < 8; c++) S[j * 256 + lane * 8 + c] = acc[j][c];
    __syncwarp();
    for (int c = lane; c < 64; c += 32) {
      float wr[5];
      for (int k = 0; k < 5; k++) wr[k] = __bfloat162float(p.wrad[k * 64 + c]);
      P[c] = wr[0] * S[c];
      P[64 + c] = wr[1] * (S[256 + 64 + c] + S[512 + 128 + c] + S[768 + 192 + c]);
      for (int i = 0; i < 3; i++) {
        P[128 + i * 192 + c] = wr[2] * S[(1 + i) * 256 + c];
        P[128 + i * 192 + 64 + c] = wr[3] * S[(1 + i) * 64 + c];
        float t = 0.f;
        for (int j = 0; j < 3; j++)
          for (int k = 0; k < 3; k++)
            t += __bfloat162float(p.eps[i * 9 + j * 3 + k]) * S[(1 + j) * 256 + (1 + k) * 64 + c];
        P[128 + i * 192 + 128 + c] = wr[4] * t;
      }
    }
    __syncwarp();
    for (int c = lane; c < 64; c += 32) {
      float a0 = 0.f, a1[3] = {0.f, 0.f, 0.f};
      for (int k = 0; k < 128; k++) a0 += P[k] * __bfloat162float(p.w0[k * 64 + c]);
      for (int k = 0; k < 192; k++) {
        const float w = __bfloat162float(p.w1[k * 64 + c]);
        for (int i = 0; i < 3; i++) a1[i] += P[128 + i * 192 + k] * w;
      }
      const float gate = 1.f / (1.f + __expf(-a0));
      p.out[(size_t)n * 256 + c] = __float2bfloat16(a0);
      for (int i = 0; i < 3; i++) p.out[(size_t)n * 256 + 64 + i * 64 + c] = __float2bfloat16(a1[i] * gate);
    }
    __syncwarp();
  }
}

struct Stage {
  uint32_t b1, b2;
  int meta;
};

__global__ void __launch_bounds__(NT, 1) eqf_kernel(const __grid_constant__ Params p) {
  extern __shared__ __align__(128) unsigned char smem[];
  const int tid = threadIdx.x, warp = tid >> 5, lane = tid & 31;
  const int bin = blockIdx.x;
  uint4* stage = reinterpret_cast<uint4*>(smem + OFF_STAGE);
  uint32_t* offs = reinterpret_cast<uint32_t*>(smem + OFF_OFFS);
  uint32_t* hist = reinterpret_cast<uint32_t*>(smem + OFF_HIST);
  uint32_t* hist2 = reinterpret_cast<uint32_t*>(smem + OFF_HIST2);
  uint32_t* loff = reinterpret_cast<uint32_t*>(smem + OFF_LOFF);
  uint32_t* delta = reinterpret_cast<uint32_t*>(smem + OFF_DELTA);
  volatile uint32_t* misc = reinterpret_cast<volatile uint32_t*>(smem + OFF_MISC);
  uint2* sc = reinterpret_cast<uint2*>(smem + OFF_SC);
  uint16_t* ss = reinterpret_cast<uint16_t*>(smem + OFF_SS);
  const uint32_t sbase = smem_u32(smem);
  const uint32_t bar_full = sbase + OFF_BAR, bar_empty = bar_full + 8 * RING;
  const uint32_t bar_in = bar_empty + 8 * RING;
  const uint32_t bar_cnt = bar_in + 8 * (1 + R1);
  const uint32_t bar_stg = bar_cnt + 8;
  const uint32_t bar_b = bar_stg + 8;
  const uint32_t bar_a1 = bar_b + 8;
  const uint32_t bar_info = bar_a1 + 8;
  uint64_t pol_stream;
  asm volatile("createpolicy.fractional.L2::evict_first.b64 %0, 1.0;" : "=l"(pol_stream));

  const int e0 = bin * CH;
  const int nE = min(CH, NE - e0);
  unsigned long long bar_target = 0;
  auto load_payload = [&](const int r) {
    const int nr = min(NT * 4, nE - r * NT * 4);
    if (nr > 0) {
      const int o = r * NT * 4;
      bulk_load(sbase + OFF_RS + o * 4, p.src + e0 + o, nr * 4, bar_in + 8 * (1 + r), pol_stream, nr * 12);
      bulk_load(sbase + OFF_RA + o * 2, p.eattr + e0 + o, nr * 2, bar_in + 8 * (1 + r), pol_stream, 0);
      bulk_load(sbase + OFF_RY + o * 6, p.rhat + (size_t)(e0 + o) * 3, nr * 6, bar_in + 8 * (1 + r), pol_stream, 0);
    }
  };
  if (tid == 0) {
    for (int s = 0; s <= R1; s++) mbar_init(bar_in + 8 * s, 1);
    asm volatile("fence.mbarrier_init.release.cluster;" ::: "memory");
    fence_async_smem();
    bulk_load(sbase + OFF_RD, p.dst + e0, nE * 4, bar_in, pol_stream, nE * 4);
#pragma unroll
    for (int r = 0; r < R1; r++) load_payload(r);
    for (int s = 0; s < RING; s++) {
      mbar_init(bar_full + 8 * s, 8);
      mbar_init(bar_empty + 8 * s, 4);
    }
    mbar_init(bar_cnt, 1);
    mbar_init(bar_stg, NTM / 32);
    mbar_init(bar_b, NTM / 32);
    mbar_init(bar_a1, 1);
    for (int s = 0; s < NPBUF; s++) mbar_init(bar_info + 8 * s, 1);
    asm volatile("fence.mbarrier_init.release.cluster;" ::: "memory");
    misc[2] = 0;
    misc[3] = 0;
    misc[4] = 0x7fffffffu;
    if (bin == 0) g_pool = 0;
  }
  unsigned long long bar_v0 = 0;
  if (tid == 0 || tid == NTM)
    asm volatile("ld.relaxed.gpu.global.u64 %0, [%1];" : "=l"(bar_v0) : "l"(&g_bar[tid == 0 ? 0 : 16]) : "memory");
  if (tid < HB) hist[tid] = 0;
  if (tid < 336) hist2[tid] = 0;
  const int wfw = bin * 78 + tid - (NT - 96);
  const bool wf_on = (tid >= NT - 96) && (tid - (NT - 96) < 78) && (wfw < 10240);
  unsigned short wf0 = 0, wf1 = 0, wf2 = 0, wf3 = 0;
  if (wf_on) {
    const int r = wfw & 3, et = (wfw >> 2) & 127, ks = (wfw >> 9) & 3, mat = wfw >> 11;
    const int m = (et >> 5) * 16 + ((et & 31) >> 2) + (r & 1) * 8;
    const int pk = ks * 16 + (r >> 1) * 8 + 2 * (et & 3);
    const int ch0 = 8 * (pk & 7) + (pk >> 3), ch1 = ch0 + 8;
    const unsigned short* W = reinterpret_cast<const unsigned short*>(mat < 2 ? p.w0 + mat * 4096 : p.w1 + (mat - 2) * 4096);
    const unsigned short* wr = reinterpret_cast<const unsigned short*>(p.wrad) + mat * 64;
    wf0 = __ldg(W + ch0 * 64 + m); wf1 = __ldg(wr + ch0);
    wf2 = __ldg(W + ch1 * 64 + m); wf3 = __ldg(wr + ch1);
  }
  __syncthreads();
  mbar_wait(bar_in, 0);
  uint32_t key[R1 * 4];
#pragma unroll
  for (int r = 0; r < R1; r++) {
    const int q = min((tid + r * NT) * 4, nE - 4);
    const int4 dv = *reinterpret_cast<const int4*>(smem + OFF_RD + q * 4);
    const bool act = (tid + r * NT) * 4 < nE;
    const int d4[4] = {dv.x, dv.y, dv.z, dv.w};
#pragma unroll
    for (int i = 0; i < 4; i++) {
      const uint32_t b0 = (uint32_t)d4[i] / NPB;
      const uint32_t dl = (uint32_t)d4[i] - b0 * NPB;
      const uint32_t b = act ? (dl >= (uint32_t)HA ? b0 + NB : b0) : (uint32_t)NH;
      const uint32_t rank = atomicAdd(&hist[b], 1u);
      key[r * 4 + i] = (b << 21) | (dl << 13) | rank;
    }
  }
  if (tid == 0 || tid == NTM) {
    bar_target = (bar_v0 / NB + 1) * NB;
    if (tid == 0) misc[6] = (uint32_t)(bar_target / NB);
  }
  __syncthreads();
  uint32_t my_cnt = 0, my_g = 0;
  if (warp == 0) {
    uint32_t c[9], s = 0;
#pragma unroll
    for (int j = 0; j < 9; j++) {
      const int b = lane * 9 + j;
      c[j] = (b < NH) ? hist[b] : 0;
      s += c[j];
    }
    uint32_t incl = s;
#pragma unroll
    for (int o = 1; o < 32; o <<= 1) {
      const uint32_t t = __shfl_up_sync(0xffffffffu, incl, o);
      if (lane >= o) incl += t;
    }
    const uint32_t gap = CH - __shfl_sync(0xffffffffu, incl, 31);
    uint32_t ex = incl - s;
#pragma unroll
    for (int j = 0; j < 9; j++) {
      const int b = lane * 9 + j;
      if (b == NB) misc[7] = ex;
      if (b <= NH) loff[b] = ex + (b >= NB ? gap : 0u);
      ex += c[j];
    }
  } else if (tid >= 128 && tid - 128 < NH) {
    my_cnt = hist[tid - 128];
    my_g = atomicAdd(&g_cnt[tid - 128], my_cnt + (1u << 20));
  }
  __syncthreads();
#pragma unroll
  for (int r = 0; r < R1; r++) {
    const int q = min((tid + r * NT) * 4, nE - 4);
    if (r * NT * 4 < nE) mbar_wait(bar_in + 8 * (1 + r), 0);
    const uint4 sv = *reinterpret_cast<const uint4*>(smem + OFF_RS + q * 4);
    const uint2 av = *reinterpret_cast<const uint2*>(smem + OFF_RA + q * 2);
    const uint2 y0 = *reinterpret_cast<const uint2*>(smem + OFF_RY + q * 6);
    const uint2 y1 = *reinterpret_cast<const uint2*>(smem + OFF_RY + q * 6 + 8);
    const uint2 y2 = *reinterpret_cast<const uint2*>(smem + OFF_RY + q * 6 + 16);
    const uint32_t s4[4] = {sv.x, sv.y, sv.z, sv.w};
    const float a4[4] = {bf_lo(av.x), bf_hi(av.x), bf_lo(av.y), bf_hi(av.y)};
    const uint32_t w[6] = {y0.x, y0.y, y1.x, y1.y, y2.x, y2.y};
#pragma unroll
    for (int i = 0; i < 4; i++) {
      const uint32_t k = key[r * 4 + i];
      float y[3];
#pragma unroll
      for (int j = 0; j < 3; j++) {
        const int h = i * 3 + j;
        y[j] = (h & 1) ? bf_hi(w[h >> 1]) : bf_lo(w[h >> 1]);
      }
      uint4 rec;
      rec.x = pack_bf16(a4[i], a4[i] * y[0]);
      rec.y = pack_bf16(a4[i] * y[1], a4[i] * y[2]);
      rec.z = s4[i] | (((k >> 13) & 0xffu) << 16);
      rec.w = k >> 21;
      if (rec.w < (uint32_t)NH) stage[loff[rec.w] + (k & 0x1fffu)] = rec;
    }
  }
  if (tid >= 128 && tid - 128 < NH) {
    const int b = tid - 128;
    my_g &= 0xfffffu;
    const uint32_t cap = (b < NB) ? CAPA : CAPB;
    const uint32_t base = (b < NB) ? b * CAPA : NB * CAPA + (b - NB) * CAPB;
    delta[b] = (my_g + my_cnt <= cap) ? base + my_g - loff[b] : 0xffffffffu;
  }
  if (wf_on) {
    const float v0 = __uint_as_float((uint32_t)wf0 << 16) * __uint_as_float((uint32_t)wf1 << 16);
    const float v1 = __uint_as_float((uint32_t)wf2 << 16) * __uint_as_float((uint32_t)wf3 << 16);
    reinterpret_cast<uint32_t*>(g_wfrag)[wfw] = pack_bf16(v0, v1);
  }
  __syncthreads();
  const int nA = (int)misc[7], b0 = (int)loff[NB];
  auto write_out = [&](const int i) {
    const uint4 rec = stage[i];
    const uint32_t d = delta[rec.w];
    if (d != 0xffffffffu) {
      asm volatile("st.global.v4.u32 [%0], {%1,%2,%3,%4};"
                   ::"l"(g_rec + (d + i)), "r"(rec.x), "r"(rec.y), "r"(rec.z), "r"(rec.w) : "memory");
    }
  };
  for (int i = tid; i < nA; i += NT) write_out(i);
  __syncthreads();

  const int n0 = bin * NPB;
  const int nn = min(NPB, NN - n0);
  const int nn8 = (nn + 7) & ~7;
  uint32_t cntA = 0, cntB = 0;

  auto sort_half = [&](auto Rc, auto NLc, const int bid, const int t0, const int half, const uint32_t cnt,
                       const uint32_t* rx, const uint32_t* ry, const uint32_t* rz) {
    constexpr int R = decltype(Rc)::value, NL = decltype(NLc)::value;
    uint32_t* h2 = hist2 + half * 168;
    const uint32_t nb0 = half * HA, sbase0 = half * SLOTA;
    uint32_t rk[R];
#pragma unroll
    for (int r = 0; r < R; r++) {
      const uint32_t i = t0 + r * NTM;
      const uint32_t dl = (i < cnt) ? (rz[r] >> 16) - nb0 : 164u;
      rk[r] = atomicAdd(&h2[dl], 1u);
    }
    asm volatile("bar.sync %0, %1;" ::"r"(bid), "n"(NTM) : "memory");
    if (t0 < 32) {
      uint32_t c[NL], s = 0;
#pragma unroll
      for (int j = 0; j < NL; j++) {
        c[j] = h2[t0 * NL + j];
        s += c[j];
      }
      uint32_t incl = s;
#pragma unroll
      for (int o = 1; o < 32; o <<= 1) {
        const uint32_t t = __shfl_up_sync(0xffffffffu, incl, o);
        if (t0 >= o) incl += t;
      }
      uint32_t ex = incl - s + sbase0;
#pragma unroll
      for (int j = 0; j < NL; j++) {
        if (half == 1 || t0 * NL + j < HA) offs[nb0 + t0 * NL + j] = ex | ((ex + c[j]) << 16);
        ex += c[j];
      }
    }
    if (t0 >= 32 && t0 < 40) {
      sc[sbase0 + cnt + (t0 - 32)] = make_uint2(0u, 0u);
      ss[sbase0 + cnt + (t0 - 32)] = 0;
    }
    asm volatile("bar.sync %0, %1;" ::"r"(bid), "n"(NTM) : "memory");
#pragma unroll
    for (int r = 0; r < R; r++) {
      const uint32_t i = t0 + r * NTM;
      if (i < cnt) {
        const uint32_t pp = (offs[rz[r] >> 16] & 0xffffu) + rk[r];
        sc[pp] = make_uint2(rx[r], ry[r]);
        ss[pp] = (uint16_t)rz[r];
      }
    }
  };

  if (tid == 0) {
    asm volatile("red.release.gpu.global.add.u64 [%0], 1;" ::"l"(&g_bar[0]) : "memory");
    mbar_arrive(bar_a1);
  }
  if (tid == 32) {
    uint32_t ca, cb;
    int it = 0;
    do {
      asm volatile("ld.relaxed.gpu.global.u32 %0, [%1];" : "=r"(ca) : "l"(&g_cnt[bin]) : "memory");
      asm volatile("ld.relaxed.gpu.global.u32 %0, [%1];" : "=r"(cb) : "l"(&g_cnt[NB + bin]) : "memory");
    } while (((ca >> 20) != NB || (cb >> 20) != NB) && ++it < (1 << 20));
    misc[0] = ca & 0xfffffu;
    misc[1] = cb & 0xfffffu;
    g_cnt[bin] = 0;
    g_cnt[NB + bin] = 0;
    mbar_arrive(bar_cnt);
  }
  if (tid >= NTM) {
    mbar_wait(bar_a1, 0);
    for (int i = b0 + tid - NTM; i < CH; i += NTM) write_out(i);
    __syncwarp();
    mbar_arrive_lane0(bar_stg, lane);
  }

  if (tid < NTM) {
    if (tid == 0) {
      unsigned long long v;
      int it = 0;
      do {
        asm volatile("ld.acquire.gpu.global.u64 %0, [%1];" : "=l"(v) : "l"(&g_bar[0]) : "memory");
      } while (v < bar_target && ++it < (1 << 22));
    }
    asm volatile("bar.sync 2, %0;" ::"n"(NTM) : "memory");
    mbar_wait(bar_cnt, 0);
    cntA = misc[0];
    cntB = misc[1];
    if (cntA <= (uint32_t)CAPA && cntB <= (uint32_t)CAPB) {
      uint32_t rx[R2A], ry[R2A], rz[R2A];
#pragma unroll
      for (int r = 0; r < R2A; r++) {
        const uint32_t i = min(tid + r * NTM, max(cntA, 1u) - 1u);
        uint4 v = make_uint4(0u, 0u, 0u, 0u);
        if (cntA) v = ldg_cg_u4(g_rec + (size_t)bin * CAPA + i, pol_stream);
        rx[r] = v.x; ry[r] = v.y; rz[r] = v.z;
      }
      sort_half(std::integral_constant<int, R2A>{}, std::integral_constant<int, NLA>{}, 2, tid, 0, cntA, rx, ry, rz);
      asm volatile("bar.sync 2, %0;" ::"n"(NTM) : "memory");
    }
  } else {
    const int tb = tid - NTM;
    asm volatile("bar.sync 3, %0;" ::"n"(NTM) : "memory");
    if (tb == 0) {
      asm volatile("red.release.gpu.global.add.u64 [%0], 1;" ::"l"(&g_bar[16]) : "memory");
      unsigned long long v;
      int it = 0;
      do {
        asm volatile("ld.acquire.gpu.global.u64 %0, [%1];" : "=l"(v) : "l"(&g_bar[16]) : "memory");
      } while (v < bar_target && ++it < (1 << 22));
    }
    asm volatile("bar.sync 3, %0;" ::"n"(NTM) : "memory");
    mbar_wait(bar_cnt, 0);
    cntA = misc[0];
    cntB = misc[1];
    if (cntA <= (uint32_t)CAPA && cntB <= (uint32_t)CAPB) {
      uint32_t rx[R2B], ry[R2B], rz[R2B];
#pragma unroll
      for (int r = 0; r < R2B; r++) {
        const uint32_t i = min(tb + r * NTM, max(cntB, 1u) - 1u);
        uint4 v = make_uint4(0u, 0u, 0u, 0u);
        if (cntB) v = ldg_cg_u4(g_rec + (size_t)NB * CAPA + (size_t)bin * CAPB + i, pol_stream);
        rx[r] = v.x; ry[r] = v.y; rz[r] = v.z;
      }
      sort_half(std::integral_constant<int, R2B>{}, std::integral_constant<int, NLB>{}, 3, tb, 1, cntB, rx, ry, rz);
      if (tb == 0) {
        int own = nn8;
        if ((nn8 >> 3) - PT >= HA / 8 + 2) {
          bool fits = true;
          for (int j = 0; j < PT; j++) {
            const int nb = nn8 - 8 * (PT - j);
            fits = fits && ((offs[nb + 7] >> 16) - (offs[nb] & 0xffffu) <= (uint32_t)PCAP);
          }
          if (fits) own = nn8 - 8 * PT;
        }
        misc[5] = (uint32_t)own;
      }
      __syncwarp();
      mbar_arrive_lane0(bar_b, lane);
    }
  }
  if (cntA > (uint32_t)CAPA || cntB > (uint32_t)CAPB) {
    mbar_wait(bar_stg, 0);
    if (warp == 0) {
      for (int i = lane; i < PT * 3; i += 32) g_ph[bin * PT * 3 + i] = make_uint4(0u, 0u, 0u, 0u);
      for (int i = lane; i < PT * PSTR / 2; i += 32) g_psc[bin * PT * (PSTR / 2) + i] = make_uint4(0u, 0u, 0u, 0u);
      for (int i = lane; i < PT * PSTR / 8; i += 32) g_pss[bin * PT * (PSTR / 8) + i] = make_uint4(0u, 0u, 0u, 0u);
      __syncwarp();
      __threadfence();
      __syncwarp();
      if (lane == 0) asm volatile("red.release.gpu.global.add.u64 [%0], 1;" ::"l"(&g_bar[32]) : "memory");
    }
    slow_path(p, smem, bin);
    return;
  }

  if (warp < GW) {
    asm volatile("setmaxnreg.dec.sync.aligned.u32 %0;" ::"n"(REG_G));
    const int g = lane >> 2, t = lane & 3, q = lane >> 3;
    const char* xq = reinterpret_cast<const char*>(p.x) + (lane & 7) * 16;
    const uint32_t xs = sbase + OFF_X + warp * NST * 4096;
    const uint32_t cd0 = xs + q * 512 + (((lane & 7) ^ q) * 16);
    const uint32_t cd1 = xs + (4 + q) * 512 + (((lane & 7) ^ (4 + q)) * 16);
    const uint32_t la0 = xs + (lane & 7) * 512 + ((q ^ (lane & 7)) * 16);
    const uint32_t la1 = xs + (lane & 7) * 512 + (((4 + q) ^ (lane & 7)) * 16);
    const uint32_t sc_s = sbase + OFF_SC + t * 16 + (g & 3) * 2;
    const uint32_t ss_s = sbase + OFF_SS + q * 2;
    const uint32_t mask1 = (g < 4) ? 0xffffffffu : 0u;
    uint32_t st[4];
#pragma unroll
    for (int c = 0; c < 4; c++) {
      const int blk = 2 * (c >> 1) + (t >> 1), jj = 2 * (t & 1) + (c & 1);
      const int a = (blk == 0) ? (jj == 0 ? 15 : 11 + jj) : (jj == 0 ? 8 + blk : 3 * (jj - 1) + (blk - 1));
      st[c] = sbase + OFF_S + a * ATOM + g * LBO_S;
    }
    float acc[8][4];
#pragma unroll
    for (int i = 0; i < 8; i++) acc[i][0] = acc[i][1] = acc[i][2] = acc[i][3] = 0.f;

    const volatile uint32_t* offv = reinterpret_cast<const volatile uint32_t*>(smem + OFF_OFFV);
    if (warp == GW - 1) {
      mbar_wait(bar_b, 0);
      const int own = (int)misc[5];
      {
        uint2* gsc = reinterpret_cast<uint2*>(g_psc);
        unsigned short* gss = reinterpret_cast<unsigned short*>(g_pss);
        uint32_t* gph = reinterpret_cast<uint32_t*>(g_ph);
#pragma unroll 1
        for (int j = 0; j < PT; j++) {
          const int e = bin * PT + j;
          uint32_t h = 0, beg = 0, cnt = 0;
          if (own < nn8) {
            const int nb = own + 8 * j;
            beg = offs[nb] & 0xffffu;
            cnt = (offs[nb + 7] >> 16) - beg;
            if (lane < 8) h = offs[nb + lane] - beg * 0x10001u;
            else if (lane == 8) h = (uint32_t)(n0 + nb);
            else if (lane == 9) h = (uint32_t)max(0, min(8, nn - nb));
          }
          for (uint32_t i = lane; i < (uint32_t)PSTR; i += 32) {
            gsc[e * PSTR + i] = (i < cnt) ? sc[beg + i] : make_uint2(0u, 0u);
            gss[e * PSTR + i] = (i < cnt) ? ss[beg + i] : (unsigned short)0;
          }
          if (lane < 12) gph[e * 12 + lane] = h;
        }
      }
      __syncwarp();
      __threadfence();
      __syncwarp();
      if (lane == 0) {
        asm volatile("red.release.gpu.global.add.u64 [%0], 1;" ::"l"(&g_bar[32]) : "memory");
        const unsigned long long pub_target = (unsigned long long)misc[6] * NB;
        {
          int it = 0;
          while ((int)misc[3] < HA / 8 && ++it < (1 << 22)) __nanosleep(200);
          unsigned long long v;
          it = 0;
          do {
            asm volatile("ld.acquire.gpu.global.u64 %0, [%1];" : "=l"(v) : "l"(&g_bar[32]) : "memory");
          } while (v < pub_target && ++it < (1 << 20));
          asm volatile("fence.proxy.async;" ::: "memory");
          it = 0;
          while ((int)misc[2] < own - LOOK && ++it < (1 << 22)) __nanosleep(32);
        }
        uint32_t k = atomicAdd(&g_pool, 1u);
        for (int qq = 0;; qq++) {
          int it = 0;
          while ((int)misc[2] < own + 8 * qq - LOOK && ++it < (1 << 22)) __nanosleep(32);
          if (qq >= NPBUF) {
            const int need = (own >> 3) + qq - NPBUF + 1;
            it = 0;
            while ((int)misc[3] < need && ++it < (1 << 22)) __nanosleep(32);
            fence_async_smem();
          }
          const int j = qq % NPBUF;
          if (k >= (uint32_t)(NB * PT)) {
            misc[4] = (uint32_t)qq;
            mbar_arrive(bar_info + 8 * j);
            break;
          }
          const uint32_t e = (k % NB) * PT + k / NB;
          bulk_load(sbase + OFF_OFFV + j * 48, &g_ph[e * 3], 48, bar_info + 8 * j, pol_stream, 48 + PSTR * 10);
          bulk_load(sbase + OFF_SS + j * PSTR * 2, &g_pss[e * (PSTR / 8)], PSTR * 2, bar_info + 8 * j, pol_stream, 0);
          bulk_load(sbase + OFF_SC + j * PSTR * 8, &g_psc[e * (PSTR / 2)], PSTR * 8, bar_info + 8 * j, pol_stream, 0);
          k = atomicAdd(&g_pool, 1u);
        }
      }
      return;
    }

    if (warp >= GA) return;
    if (OFF_STAGE + b0 * 16 < OFF_X + (warp + 1) * NST * 4096) mbar_wait(bar_stg, 0);
    bool s_free = false;
    int node, pos, end, pend;
    int own = HA;
    bool b_ready = false;
    auto resolve = [&]() {
      const int n = pend;
      uint32_t be;
      if (n < own) {
        be = offs[n];
      } else {
        const int qq = (n - own) >> 3, j = qq % NPBUF;
        const bool ready = __all_sync(0xffffffffu, mbar_try(bar_info + 8 * j, (qq / NPBUF) & 1));
        const int stop = __shfl_sync(0xffffffffu, (int)misc[4], 0);
        if (stop < qq || (ready && stop == qq)) {
          node = -1;
          return;
        }
        if (!ready) { node = -2; return; }
        be = offv[j * 12 + (n & 7)] + (uint32_t)(j * PSTR) * 0x10001u;
      }
      node = n;
      pos = (int)(be & 0xffffu);
      end = (int)(be >> 16);
    };
    auto next_node = [&]() {
      int n = 0;
      asm volatile("{\n.reg .pred p;\nsetp.eq.s32 p, %2, 0;\n@p atom.shared.add.u32 %0, [%1], 1;\n}"
                   : "+r"(n) : "r"(sbase + OFF_MISC + 8), "r"(lane) : "memory");
      n = __shfl_sync(0xffffffffu, n, 0);
      if (n >= HA && !b_ready) {
        mbar_wait(bar_b, 0);
        own = (int)misc[5];
        b_ready = true;
      }
      pend = n;
      resolve();
    };
    auto issue = [&](Stage& B, const int i) {
      if (node == -2) resolve();
      if (node < 0) {
        B.meta = node;
        asm volatile("cp.async.commit_group;" ::: "memory");
        return;
      }
      const int cnt = end - pos;
      const bool last = (cnt <= 8);
      B.meta = node | (last ? 0x10000 : 0);
      uint32_t s0, s1, c0, c1;
      asm volatile("ld.shared.u16 %0, [%1];" : "=r"(s0) : "r"(ss_s + pos * 2));
      asm volatile("ld.shared.u16 %0, [%1+8];" : "=r"(s1) : "r"(ss_s + pos * 2));
      asm volatile("ld.shared.u16 %0, [%1];" : "=r"(c0) : "r"(sc_s + pos * 8));
      asm volatile("ld.shared.u16 %0, [%1+8];" : "=r"(c1) : "r"(sc_s + pos * 8));
      const int z0 = (q < cnt) ? 16 : 0, z1 = (4 + q < cnt) ? 16 : 0;
      const char* p0 = xq + (size_t)s0 * 512;
      const char* p1 = xq + (size_t)s1 * 512;
#pragma unroll
      for (int k = 0; k < 4; k++) {
        asm volatile("cp.async.cg.shared.global [%0], [%1], 16, %2;" ::"r"(cd0 + i * 4096 + k * 128), "l"(p0 + k * 128), "r"(z0) : "memory");
        asm volatile("cp.async.cg.shared.global [%0], [%1], 16, %2;" ::"r"(cd1 + i * 4096 + k * 128), "l"(p1 + k * 128), "r"(z1) : "memory");
      }
      asm volatile("cp.async.commit_group;" ::: "memory");
      const uint32_t m = __funnelshift_lc(0xffffffffu, 0u, (uint32_t)max(16 * min(cnt, 8) - 32 * t, 0));
      const uint32_t b = (c0 | (c1 << 16)) & m;
      B.b1 = b & mask1;
      B.b2 = b & ~mask1;
      pos += 8;
      if (last) next_node();
    };
    auto consume = [&](Stage& B, const int i) {
      asm volatile("cp.async.wait_group %0;" ::"n"(NST - 1) : "memory");
      if (B.meta < 0) return;
      __syncwarp();
#pragma unroll
      for (int j = 0; j < 8; j++) {
        uint32_t r0, r1, r2, r3;
        asm volatile("ldmatrix.sync.aligned.m8n8.x4.trans.shared.b16 {%0,%1,%2,%3}, [%4];"
                     : "=r"(r0), "=r"(r1), "=r"(r2), "=r"(r3)
                     : "r"(((j & 1) ? la1 : la0) + i * 4096 + (j >> 1) * 128) : "memory");
        const int blk = j >> 1;
        const uint32_t b = (blk & 1) ? B.b2 : B.b1;
        mma16808(acc[(blk >> 1) * 4 + (j & 1) * 2 + 0], r0, r1, b);
        mma16808(acc[(blk >> 1) * 4 + (j & 1) * 2 + 1], r2, r3, b);
      }
      if (B.meta & 0x10000) {
        const int n = B.meta & 0xffff;
        const int tl = n >> 3;
        const int slot = tl % RING;
        if (!s_free) {
          mbar_wait(bar_stg, 0);
          s_free = true;
        }
        mbar_wait(bar_empty + 8 * slot, ((tl / RING) & 1) ^ 1);
        const uint32_t o = slot * TILE + (n & 7) * 16;
#pragma unroll
        for (int c = 0; c < 4; c++) {
          uint32_t w[4];
#pragma unroll
          for (int u = 0; u < 4; u++) {
            const float* a = acc[(c >> 1) * 4 + u];
            w[u] = pack_bf16(a[c & 1], a[2 + (c & 1)]);
          }
          asm volatile("st.shared.v4.u32 [%0], {%1,%2,%3,%4};" ::"r"(st[c] + o), "r"(w[0]), "r"(w[1]), "r"(w[2]), "r"(w[3]) : "memory");
        }
#pragma unroll
        for (int u = 0; u < 8; u++) acc[u][0] = acc[u][1] = acc[u][2] = acc[u][3] = 0.f;
        __syncwarp();
        mbar_arrive_lane0(bar_full + 8 * slot, lane);
      }
      __syncwarp();
    };

    Stage B[NST];
    next_node();
#pragma unroll
    for (int i = 0; i < NST; i++) issue(B[i], i);
    bool run = true;
    int guard = 0;
    while (run && ++guard < (1 << 24)) {
#pragma unroll
      for (int i = 0; i < NST; i++) {
        if (B[i].meta == -1) { run = false; break; }
        consume(B[i], i);
        issue(B[i], i);
      }
    }
  } else {
    asm volatile("setmaxnreg.inc.sync.aligned.u32 %0;" ::"n"(REG_E));
    const int et = tid - GW * 32, ew = et >> 5;
    uint32_t wa[5][4][4];
#pragma unroll
    for (int mat = 0; mat < 5; mat++) {
#pragma unroll
      for (int ks = 0; ks < 4; ks++) {
        const uint4 v = __ldcg(&g_wfrag[(mat * 4 + ks) * 128 + et]);
        wa[mat][ks][0] = v.x; wa[mat][ks][1] = v.y; wa[mat][ks][2] = v.z; wa[mat][ks][3] = v.w;
      }
    }
    float* eps = reinterpret_cast<float*>(smem + OFF_EPS);
    if (et < 27) eps[et] = __bfloat162float(p.eps[et]);
    asm volatile("bar.sync 1, 128;" ::: "memory");

    mbar_wait(bar_b, 0);
    const int own = (int)misc[5];
    const int town = own >> 3;
    const volatile uint32_t* offv = reinterpret_cast<const volatile uint32_t*>(smem + OFF_OFFV);
    for (int tl = 0;; tl++) {
      const int slot = tl % RING;
      int row0 = n0 + tl * 8, nvalid = nn - tl * 8;
      if (tl >= town) {
        const int qq = tl - town, j = qq % NPBUF;
        bool ready = false;
        int stop = 0x7fffffff;
        for (int it = 0; it < (1 << 22); it++) {
          ready = __all_sync(0xffffffffu, mbar_try(bar_info + 8 * j, (qq / NPBUF) & 1));
          stop = __shfl_sync(0xffffffffu, (int)misc[4], 0);
          if (ready || stop < qq) break;
        }
        if (stop <= qq || !ready) break;
        row0 = (int)offv[j * 12 + 8];
        nvalid = (int)offv[j * 12 + 9];
      }
      mbar_wait(bar_full + 8 * slot, (tl / RING) & 1);
      fence_async_smem();
      const uint32_t tb = sbase + OFF_S + slot * TILE;
      float d0[4], dt[12], d1[12], q[36];
      asm volatile("wgmma.fence.sync.aligned;" ::: "memory");
#pragma unroll
      for (int ks = 0; ks < 4; ks++) {
        wgmma_n72(q, wa[4][ks], make_desc(tb + ks * 2 * LBO_S, LBO_S, ATOM), ks);
        wgmma_n24(dt, wa[1][ks], make_desc(tb + ks * 2 * LBO_S, LBO_S, 4 * ATOM), ks);
        wgmma_n8(d0, wa[0][ks], make_desc(tb + 15 * ATOM + ks * 2 * LBO_S, LBO_S, ATOM), ks);
        wgmma_n24(d1, wa[2][ks], make_desc(tb + 12 * ATOM + ks * 2 * LBO_S, LBO_S, ATOM), ks);
      }
#pragma unroll
      for (int ks = 0; ks < 4; ks++)
        wgmma_n24(d1, wa[3][ks], make_desc(tb + 9 * ATOM + ks * 2 * LBO_S, LBO_S, ATOM), 1);
      asm volatile("wgmma.commit_group.sync.aligned;" ::: "memory");
      asm volatile("wgmma.wait_group.sync.aligned 0;" ::: "memory");
      mbar_arrive_lane0(bar_empty + 8 * slot, lane);

      float gate[4];
#pragma unroll
      for (int xx = 0; xx < 4; xx++) {
        d0[xx] += dt[xx] + dt[4 + xx] + dt[8 + xx];
        gate[xx] = __fdividef(1.f, 1.f + __expf(-d0[xx]));
      }
      uint32_t R[4][2];
      R[0][0] = pack_bf16(d0[0], d0[1]);
      R[0][1] = pack_bf16(d0[2], d0[3]);
#pragma unroll
      for (int i = 0; i < 3; i++) {
        float o[4] = {d1[4 * i], d1[4 * i + 1], d1[4 * i + 2], d1[4 * i + 3]};
#pragma unroll
        for (int m = 0; m < 9; m++) {
          const float e = eps[i * 9 + m];
#pragma unroll
          for (int xx = 0; xx < 4; xx++) o[xx] = fmaf(e, q[4 * m + xx], o[xx]);
        }
        R[1 + i][0] = pack_bf16(o[0] * gate[0], o[1] * gate[1]);
        R[1 + i][1] = pack_bf16(o[2] * gate[2], o[3] * gate[3]);
      }
      const uint32_t ob = sbase + OFF_OUT + (tl & 1) * 8 * OROW;
      {
        const int mi = lane >> 3, j = lane & 7;
        const uint32_t a = ob + j * OROW + ((mi >> 1) * 64 + ew * 16 + (mi & 1) * 8) * 2;
        asm volatile("stmatrix.sync.aligned.m8n8.x4.trans.shared.b16 [%0], {%1,%2,%3,%4};"
                     ::"r"(a), "r"(R[0][0]), "r"(R[0][1]), "r"(R[1][0]), "r"(R[1][1]) : "memory");
        asm volatile("stmatrix.sync.aligned.m8n8.x4.trans.shared.b16 [%0], {%1,%2,%3,%4};"
                     ::"r"(a + 256), "r"(R[2][0]), "r"(R[2][1]), "r"(R[3][0]), "r"(R[3][1]) : "memory");
      }
      asm volatile("bar.sync 1, 128;" ::: "memory");
      if (et == 0) misc[3] = (uint32_t)(tl + 1);
#pragma unroll
      for (int h = 0; h < 2; h++) {
        const int c = et + 128 * h, row = c >> 5, c16 = c & 31;
        if (row < nvalid) {
          const uint4 v = *reinterpret_cast<const uint4*>(smem + OFF_OUT + (tl & 1) * 8 * OROW + row * OROW + c16 * 16);
          asm volatile("st.global.L2::cache_hint.v4.u32 [%0], {%1,%2,%3,%4}, %5;"
                       ::"l"(reinterpret_cast<char*>(p.out) + (size_t)(row0 + row) * 512 + c16 * 16),
                         "r"(v.x), "r"(v.y), "r"(v.z), "r"(v.w), "l"(pol_stream) : "memory");
        }
      }
    }
  }
}

__global__ void __launch_bounds__(NT, 1) eqf_slow_kernel(const __grid_constant__ Params p) {
  extern __shared__ __align__(128) unsigned char smem[];
  slow_path(p, smem, blockIdx.x);
}

}

extern "C" void kernel_launch(void* const* d_in, const int* in_sizes, int n_in, void* d_out, int out_size) {
  using namespace eqf;
  if (n_in < 9 || in_sizes[0] != NN * 256 || in_sizes[1] != NE * 3 || in_sizes[2] != NE || in_sizes[3] != NE ||
      in_sizes[4] != NE || out_size != NN * 256) {
    fprintf(stderr, "kernel_launch: unexpected problem size\n");
    return;
  }
  static int mode = -1;
  if (mode < 0) {
    int dev = 0, sms = 0, occ = 0;
    cudaGetDevice(&dev);
    cudaDeviceGetAttribute(&sms, cudaDevAttrMultiProcessorCount, dev);
    cudaFuncSetAttribute(eqf_kernel, cudaFuncAttributeMaxDynamicSharedMemorySize, SMEM_BYTES);
    cudaFuncSetAttribute(eqf_slow_kernel, cudaFuncAttributeMaxDynamicSharedMemorySize, (NT / 32) * 1792 * 4);
    cudaOccupancyMaxActiveBlocksPerMultiprocessor(&occ, eqf_kernel, NT, SMEM_BYTES);
    mode = (sms * occ >= NB) ? 1 : 0;
  }
  Params p;
  p.x = (const __nv_bfloat16*)d_in[0];
  p.rhat = (const __nv_bfloat16*)d_in[1];
  p.eattr = (const __nv_bfloat16*)d_in[2];
  p.src = (const int*)d_in[3];
  p.dst = (const int*)d_in[4];
  p.wrad = (const __nv_bfloat16*)d_in[5];
  p.w0 = (const __nv_bfloat16*)d_in[6];
  p.w1 = (const __nv_bfloat16*)d_in[7];
  p.eps = (const __nv_bfloat16*)d_in[8];
  p.out = (__nv_bfloat16*)d_out;
  if (mode == 1) eqf_kernel<<<NB, NT, SMEM_BYTES>>>(p);
  else eqf_slow_kernel<<<NB, NT, (NT / 32) * 1792 * 4>>>(p);
}
```
